```python
import torch

def _softmax(x, axis=-1):
    return torch.softmax(x, dim=axis)

def _gelu(x):
    return torch.nn.functional.gelu(x, approximate='tanh')

def _silu(x):
    return torch.nn.functional.silu(x)

def _sigmoid(x):
    return torch.sigmoid(x)

def _layernorm(x, axis=-1, eps=1e-05):
    m = x.mean(dim=axis, keepdim=True)
    v = x.var(dim=axis, keepdim=True, unbiased=False)
    return (x - m) / torch.sqrt(v + eps)

def _scatter_add(tgt, idx, src, axis=0):
    return tgt.clone().index_add_(axis, idx, src)

def _segment_sum(src, seg, n):
    out = torch.zeros((n,) + src.shape[1:], dtype=src.dtype)
    return out.index_add_(0, seg, src)

def _pad(x, pw):
    flat = tuple((v for pair in reversed(pw) for v in pair))
    return torch.nn.functional.pad(x, flat)
kernel_name = 'recurrent_scan__mha_block_cached__mixer_gmlp__prompt'

def setup_inputs():

    _w = lambda a: (lambda t: t.to(torch.bfloat16) if t.is_floating_point() else t)(torch.as_tensor(a))

    def _A_setup():
        B, Sq, D = (1, 2048, 1024)
        H, Sk, Dh = (32, 2048, 128)
        return {'x': _w((lambda *s: torch.randn(*s, dtype=torch.bfloat16) * 0.05)(B, Sq, D)), 'k_cache': _w((lambda *s: torch.randn(*s, dtype=torch.bfloat16) * 0.8)(B, H, Sk, Dh)), 'v_cache': _w((lambda *s: torch.randn(*s, dtype=torch.bfloat16) * 0.2)(B, H, Sk, Dh)), 'wq': _w((lambda *s: torch.randn(*s, dtype=torch.bfloat16) * 0.8)(D, H * Dh) * D ** (-0.5)), 'wo': _w((lambda *s: torch.randn(*s, dtype=torch.bfloat16) * 0.2)(H * Dh, D) * (H * Dh) ** (-0.5))}
    _A_in = _A_setup()

    def _B_setup():
        B, S, D, F = (1, 2048, 1024, 3584)
        Fh = F // 2
        return {'x': _w((lambda *s: torch.randn(*s, dtype=torch.bfloat16) * 0.05)(B, S, D)), 'w_in': _w((lambda *s: torch.randn(*s, dtype=torch.bfloat16) * 0.4)(D, 2 * Fh)), 'w_sp': _w(0.01 * (lambda *s: torch.randn(*s, dtype=torch.bfloat16) * 0.4)(S, S)), 'b_sp': _w(1.0 + 0.01 * (lambda *s: torch.randn(*s, dtype=torch.bfloat16) * 0.1)(S)), 'w_out': _w((lambda *s: torch.randn(*s, dtype=torch.bfloat16) * 0.1)(Fh, D))}
    _B_in = _B_setup()
    return {'A_x': _A_in['x'], 'A_k_cache': _A_in['k_cache'], 'A_v_cache': _A_in['v_cache'], 'A_wq': _A_in['wq'], 'A_wo': _A_in['wo'], 'B_x': _B_in['x'], 'B_w_in': _B_in['w_in'], 'B_w_sp': _B_in['w_sp'], 'B_b_sp': _B_in['b_sp'], 'B_w_out': _B_in['w_out']}

def reference(A_x, A_k_cache, A_v_cache, A_wq, A_wo, B_x, B_w_in, B_w_sp, B_b_sp, B_w_out):

    def _A_ref(x, k_cache, v_cache, wq, wo):
        B, Sq, D = x.shape
        H, Dh = (32, 128)
        q = (lambda x, *d: x.permute(*d))((x @ wq).reshape(B, Sq, H, Dh), 0, 2, 1, 3)
        scores = torch.einsum('bhqd,bhkd->bhqk', q, k_cache) * Dh ** (-0.5)
        p = _softmax(scores, axis=-1)
        o = torch.einsum('bhqk,bhkd->bhqd', p, v_cache)
        return (lambda x, *d: x.permute(*d))(o, 0, 2, 1, 3).reshape(B, Sq, H * Dh) @ wo

    def _B_ref(x, w_in, w_sp, b_sp, w_out):
        B, S, D = x.shape
        F = w_in.shape[-1]
        Fh = F // 2
        z = _gelu(torch.einsum('bsd,df->bsf', x, w_in))
        z1 = z[..., :Fh].clone()
        z2 = _layernorm(z[..., Fh:], axis=-1)
        g = torch.einsum('ts,bsf->btf', w_sp, z2) + b_sp[None, :, None]
        return torch.einsum('bsf,fd->bsd', z1 * g, w_out)
    x = A_x
    xn = _layernorm(x, axis=-1)
    s = _A_ref(xn, A_k_cache, A_v_cache, A_wq, A_wo)
    g = _silu(_B_ref(xn, B_w_in, B_w_sp, B_b_sp, B_w_out))
    return x + s * g
```

```cpp
#include <cuda_runtime.h>
#include <cuda_bf16.h>
#include <cuda.h>
#include <stdint.h>

namespace {

constexpr int S_ = 2048, D_ = 1024, H_ = 32, DH_ = 128, FH_ = 1792, F_ = 3584;
constexpr int NPAIR = 66;
constexpr int MAX_ITEMS = 8;

constexpr uint32_t SLOT = 16384;
constexpr uint32_t RING_BYTES = 12 * SLOT;
constexpr uint32_t STG_OFF = RING_BYTES;
constexpr uint32_t BAR_OFF = STG_OFF + 2 * SLOT;
constexpr uint32_t SMEM_BYTES = BAR_OFF + 256;
constexpr uint32_t B_FULL = 0;
constexpr uint32_t B_EMPTY = 10;
constexpr uint32_t B_STG_FULL = 20;
constexpr uint32_t B_STG_EMPTY = 22;
constexpr uint32_t B_FLAG = 24;

enum : uint32_t { T_END = 0, T_Z2 = 1, T_ATT = 2, T_SP = 3, T_FX = 4, T_FY = 5 };
__host__ __device__ constexpr uint32_t mk_item(uint32_t t, uint32_t p, uint32_t j, uint32_t k0 = 0, uint32_t k1 = 0) {
    return t | (p << 3) | (j << 6) | (k0 << 10) | (k1 << 17);
}
__device__ __forceinline__ uint32_t it_type(uint32_t it) { return it & 7; }
__device__ __forceinline__ uint32_t it_p(uint32_t it) { return (it >> 3) & 7; }
__device__ __forceinline__ uint32_t it_j(uint32_t it) { return (it >> 6) & 15; }
__device__ __forceinline__ uint32_t it_k0(uint32_t it) { return (it >> 10) & 127; }
__device__ __forceinline__ uint32_t it_k1(uint32_t it) { return (it >> 17) & 127; }

enum { M_XN = 0, M_WSP, M_O_LD, M_H_LD, M_X, M_K,
       M_WQ, M_WIN, M_WO, M_WOUT, M_Z2, M_V, M_O_ST, M_H_ST, M_OUT,
       M_COUNT };

struct Params {
    CUtensorMap maps[M_COUNT];
    const __nv_bfloat16* x;
    const __nv_bfloat16* b_sp;
    uint32_t sched[NPAIR][MAX_ITEMS];
};

__device__ __align__(1024) __nv_bfloat16 g_xn[S_ * D_];
__device__ __align__(1024) __nv_bfloat16 g_z2[S_ * FH_];
__device__ __align__(1024) __nv_bfloat16 g_o[S_ * H_ * DH_];
__device__ __align__(1024) __nv_bfloat16 g_h[S_ * FH_];
__device__ __align__(1024) float g_part[S_ * D_];
constexpr int C_XN = 0;
constexpr int C_Z2 = 32;
constexpr int C_Z2N = 64;
constexpr int C_H = 96;
constexpr int C_PART = 128;
constexpr int C_O = 256;
constexpr int C_EXIT = 256 + 512;
__device__ __align__(128) uint32_t g_cnt[1024];

#define TL(w, i) do {} while (0)
#define TLC(i) do {} while (0)

#define AT(j, i) do {} while (0)

__device__ __forceinline__ uint32_t smem_u32(const void* p) { return (uint32_t)__cvta_generic_to_shared(p); }

#define UNLIKELY(x) __builtin_expect(!!(x), 0)
__device__ __forceinline__ void die() { asm volatile("trap;\nexit;"); __builtin_unreachable(); }

__device__ __forceinline__ uint32_t mbar_try(uint32_t bar, uint32_t parity) {
    uint32_t ok;
    asm volatile("{\n.reg .pred p;\nmbarrier.try_wait.parity.shared::cta.b64 p, [%1], %2;\nselp.u32 %0, 1, 0, p;\n}"
                 : "=r"(ok) : "r"(bar), "r"(parity) : "memory");
    return ok;
}
__device__ __forceinline__ uint32_t mbar_test(uint32_t bar, uint32_t parity) {
    uint32_t ok;
    asm volatile("{\n.reg .pred p;\nmbarrier.test_wait.parity.shared::cta.b64 p, [%1], %2;\nselp.u32 %0, 1, 0, p;\n}"
                 : "=r"(ok) : "r"(bar), "r"(parity) : "memory");
    return ok;
}
__device__ __forceinline__ void mbar_wait(uint32_t bar, uint32_t parity) {
    if (UNLIKELY(!mbar_try(bar, parity))) {
        uint32_t t0 = (uint32_t)clock();
        while (!mbar_try(bar, parity)) {
            if ((uint32_t)clock() - t0 > 2000000000u) die();
        }
    }
}
__device__ __forceinline__ void mbar_arrive(uint32_t bar) {
    asm volatile("mbarrier.arrive.shared::cta.b64 _, [%0];" :: "r"(bar) : "memory");
}
__device__ __forceinline__ void mbar_arrive_cluster(uint32_t cluster_addr) {
    asm volatile("mbarrier.arrive.shared::cluster.b64 _, [%0];" :: "r"(cluster_addr) : "memory");
}
__device__ __forceinline__ void mbar_expect_tx(uint32_t bar, uint32_t bytes) {
    asm volatile("mbarrier.arrive.expect_tx.shared::cta.b64 _, [%0], %1;" :: "r"(bar), "r"(bytes) : "memory");
}
__device__ __forceinline__ void tma_2d(uint32_t dst, const CUtensorMap* m, int c0, int c1, uint32_t bar) {
    asm volatile("cp.async.bulk.tensor.2d.shared::cluster.global.mbarrier::complete_tx::bytes [%0], [%1, {%3, %4}], [%2];"
                 :: "r"(dst), "l"(m), "r"(bar), "r"(c0), "r"(c1) : "memory");
}
__device__ __forceinline__ void tma_2d_mc(uint32_t dst, const CUtensorMap* m, int c0, int c1, uint32_t bar) {
    asm volatile("cp.async.bulk.tensor.2d.shared::cluster.global.mbarrier::complete_tx::bytes.multicast::cluster [%0], [%1, {%3, %4}], [%2], %5;"
                 :: "r"(dst), "l"(m), "r"(bar), "r"(c0), "r"(c1), "h"((uint16_t)3) : "memory");
}
__device__ __forceinline__ void tma_3d_mc(uint32_t dst, const CUtensorMap* m, int c1, int c2, uint32_t bar) {
    asm volatile("cp.async.bulk.tensor.3d.shared::cluster.global.mbarrier::complete_tx::bytes.multicast::cluster [%0], [%1, {%3, %4, %5}], [%2], %6;"
                 :: "r"(dst), "l"(m), "r"(bar), "r"(0), "r"(c1), "r"(c2), "h"((uint16_t)3) : "memory");
}
__device__ __forceinline__ void bulk_ld(uint32_t dst, const void* src, uint32_t bytes, uint32_t bar) {
    asm volatile("cp.async.bulk.shared::cluster.global.mbarrier::complete_tx::bytes [%0], [%1], %2, [%3];"
                 :: "r"(dst), "l"(src), "r"(bytes), "r"(bar) : "memory");
}
__device__ __forceinline__ void tma_3d_store(const CUtensorMap* m, uint32_t src, int c1, int c2) {
    asm volatile("cp.async.bulk.tensor.3d.global.shared::cta.bulk_group [%0, {%2, %3, %4}], [%1];"
                 :: "l"(m), "r"(src), "r"(0), "r"(c1), "r"(c2) : "memory");
}
__device__ __forceinline__ uint32_t ld_relaxed(const uint32_t* p) {
    uint32_t v;
    asm volatile("ld.relaxed.gpu.global.u32 %0, [%1];" : "=r"(v) : "l"(p) : "memory");
    return v;
}
__device__ __forceinline__ void fence_acquire() { asm volatile("fence.acquire.gpu;" ::: "memory"); }
__device__ __forceinline__ void red_release(uint32_t* p) {
    asm volatile("red.release.gpu.global.add.u32 [%0], 1;" :: "l"(p) : "memory");
}
__device__ __forceinline__ void fence_proxy_async_all() { asm volatile("fence.proxy.async.global;" ::: "memory"); }
__device__ __forceinline__ void fence_proxy_async_smem() { asm volatile("fence.proxy.async.shared::cta;" ::: "memory"); }

__device__ __forceinline__ void poll_mask(const uint32_t* base, uint32_t n, uint32_t target, uint32_t need,
                                          uint32_t& mask, uint32_t lane) {
    if ((mask >> need) & 1) return;
    uint32_t t0 = (uint32_t)clock();
    while (true) {
        uint32_t ok = 0;
        if (lane < n) ok = (int32_t)(ld_relaxed(base + lane) - target) >= 0;
        mask = __ballot_sync(0xffffffffu, ok);
        if ((mask >> need) & 1) break;
        __nanosleep(64);
        if ((uint32_t)clock() - t0 > 2000000000u) die();
    }
    fence_acquire();
    __syncwarp();
    fence_proxy_async_all();
}
__device__ __forceinline__ void poll_one(const uint32_t* p, uint32_t target) {
    uint32_t t0 = (uint32_t)clock();
    while ((int32_t)(ld_relaxed(p) - target) < 0) {
        __nanosleep(32);
        if ((uint32_t)clock() - t0 > 2000000000u) die();
    }
    fence_acquire();
    fence_proxy_async_all();
}

#define WG_FENCE() asm volatile("wgmma.fence.sync.aligned;" ::: "memory")
#define WG_COMMIT() asm volatile("wgmma.commit_group.sync.aligned;" ::: "memory")
#define WG_WAIT(n) asm volatile("wgmma.wait_group.sync.aligned %0;" :: "n"(n) : "memory")

#define SCHED_FENCE() asm volatile("pmevent 0;" ::: "memory")

constexpr uint32_t DESC_HI = (1024u >> 4) | (1u << 30);
__device__ __forceinline__ uint64_t mk_desc(uint32_t lo) { return ((uint64_t)DESC_HI << 32) | lo; }
__device__ __forceinline__ uint32_t desc_lo_k(uint32_t addr) { return ((addr & 0x3FFFF) >> 4) | (1u << 16); }
__device__ __forceinline__ uint32_t desc_lo_mn(uint32_t addr) { return ((addr & 0x3FFFF) >> 4) | ((8192u >> 4) << 16); }

#define R8(d, i) "+f"(d[i]), "+f"(d[i + 1]), "+f"(d[i + 2]), "+f"(d[i + 3]), "+f"(d[i + 4]), "+f"(d[i + 5]), "+f"(d[i + 6]), "+f"(d[i + 7])

template <int N> __device__ __forceinline__ void pin(float (&d)[N]) {
#pragma unroll
    for (int i = 0; i < N; i++) asm volatile("" : "+f"(d[i]) :: "memory");
}
template <int N> __device__ __forceinline__ void pin(uint32_t (&d)[N]) {
#pragma unroll
    for (int i = 0; i < N; i++) asm volatile("" : "+r"(d[i]) :: "memory");
}

#define W8(d, i) R8(d, i)
#define REGS64 "%0,%1,%2,%3,%4,%5,%6,%7,%8,%9,%10,%11,%12,%13,%14,%15," \
        "%16,%17,%18,%19,%20,%21,%22,%23,%24,%25,%26,%27,%28,%29,%30,%31," \
        "%32,%33,%34,%35,%36,%37,%38,%39,%40,%41,%42,%43,%44,%45,%46,%47," \
        "%48,%49,%50,%51,%52,%53,%54,%55,%56,%57,%58,%59,%60,%61,%62,%63"
#define REGS128 REGS64 "," \
        "%64,%65,%66,%67,%68,%69,%70,%71,%72,%73,%74,%75,%76,%77,%78,%79," \
        "%80,%81,%82,%83,%84,%85,%86,%87,%88,%89,%90,%91,%92,%93,%94,%95," \
        "%96,%97,%98,%99,%100,%101,%102,%103,%104,%105,%106,%107,%108,%109,%110,%111," \
        "%112,%113,%114,%115,%116,%117,%118,%119,%120,%121,%122,%123,%124,%125,%126,%127"

__device__ __forceinline__ void wgmma_n256(float (&d)[128], uint64_t da, uint64_t db) {
    asm volatile("wgmma.mma_async.sync.aligned.m64n256k16.f32.bf16.bf16 {" REGS128 "}, %128, %129, 1, 1, 1, 0, 1;\n"
        : R8(d, 0), R8(d, 8), R8(d, 16), R8(d, 24), R8(d, 32), R8(d, 40), R8(d, 48), R8(d, 56),
          R8(d, 64), R8(d, 72), R8(d, 80), R8(d, 88), R8(d, 96), R8(d, 104), R8(d, 112), R8(d, 120)
        : "l"(da), "l"(db));
}
template <int TB>
__device__ __forceinline__ void wgmma_n128_rs(float (&d)[64], uint32_t a0, uint32_t a1, uint32_t a2, uint32_t a3,
                                              uint64_t db, uint32_t acc) {
    asm volatile("{\n.reg .pred p;\nsetp.ne.b32 p, %69, 0;\n"
        "wgmma.mma_async.sync.aligned.m64n128k16.f32.bf16.bf16 {" REGS64 "}, {%64,%65,%66,%67}, %68, p, 1, 1, %70;\n}\n"
        : R8(d, 0), R8(d, 8), R8(d, 16), R8(d, 24), R8(d, 32), R8(d, 40), R8(d, 48), R8(d, 56)
        : "r"(a0), "r"(a1), "r"(a2), "r"(a3), "l"(db), "r"(acc), "n"(TB));
}
template <int TB>
__device__ __forceinline__ void wgmma_n128_rs_init(float (&d)[64], uint32_t a0, uint32_t a1, uint32_t a2, uint32_t a3,
                                                   uint64_t db) {
    asm volatile("wgmma.mma_async.sync.aligned.m64n128k16.f32.bf16.bf16 {" REGS64 "}, {%64,%65,%66,%67}, %68, 0, 1, 1, %69;\n"
        : W8(d, 0), W8(d, 8), W8(d, 16), W8(d, 24), W8(d, 32), W8(d, 40), W8(d, 48), W8(d, 56)
        : "r"(a0), "r"(a1), "r"(a2), "r"(a3), "l"(db), "n"(TB));
}

__device__ __forceinline__ uint32_t pack_bf16(float lo, float hi) {
    uint32_t r;
    asm("cvt.rn.bf16x2.f32 %0, %1, %2;" : "=r"(r) : "f"(hi), "f"(lo));
    return r;
}
__device__ __forceinline__ float bf_lo(uint32_t v) { return __uint_as_float(v << 16); }
__device__ __forceinline__ float bf_hi(uint32_t v) { return __uint_as_float(v & 0xffff0000u); }
__device__ __forceinline__ float bf_round(float f) { return __bfloat162float(__float2bfloat16_rn(f)); }
__device__ __forceinline__ float ex2(float x) { float y; asm("ex2.approx.ftz.f32 %0, %1;" : "=f"(y) : "f"(x)); return y; }
__device__ __forceinline__ float tanh_fast(float x) { float y; asm("tanh.approx.f32 %0, %1;" : "=f"(y) : "f"(x)); return y; }
__device__ __forceinline__ float gelu_tanh(float x) {
    float u = x * fmaf(x * x, 0.044715f * 0.7978845608028654f, 0.7978845608028654f);
    float hx = 0.5f * x;
    return fmaf(hx, tanh_fast(u), hx);
}
__device__ __forceinline__ float silu(float x) {
    float e = ex2(-1.4426950408889634f * x);
    return __fdividef(x, 1.0f + e);
}
__device__ __forceinline__ void stsm4(uint32_t addr, uint32_t r0, uint32_t r1, uint32_t r2, uint32_t r3) {
    asm volatile("stmatrix.sync.aligned.m8n8.x4.shared.b16 [%0], {%1,%2,%3,%4};"
                 :: "r"(addr), "r"(r0), "r"(r1), "r"(r2), "r"(r3) : "memory");
}
__device__ __forceinline__ void ldsm4(uint32_t addr, uint32_t& r0, uint32_t& r1, uint32_t& r2, uint32_t& r3) {
    asm volatile("ldmatrix.sync.aligned.m8n8.x4.shared.b16 {%0,%1,%2,%3}, [%4];"
                 : "=r"(r0), "=r"(r1), "=r"(r2), "=r"(r3) : "r"(addr) : "memory");
}

__device__ __forceinline__ uint32_t g2a(uint32_t g) { return (3 * g + 1) >> 1; }
__device__ __forceinline__ uint32_t a2g(uint32_t a) { return ((2 * a + 2) / 3) & 3; }

__device__ __forceinline__ void ln_scalars(float mean, float var, float& mb, float& rden) {
    mb = bf_round(mean);
    float vb = bf_round(bf_round(var) + 1e-5f);
    float sq;
    asm("sqrt.approx.f32 %0, %1;" : "=f"(sq) : "f"(vb));
    rden = __fdividef(1.0f, bf_round(sq));
}
__device__ __forceinline__ uint32_t ln_apply(uint32_t v, float mb, float rden) {
    uint32_t d = pack_bf16(bf_lo(v) - mb, bf_hi(v) - mb);
    return pack_bf16(bf_lo(d) * rden, bf_hi(d) * rden);
}
__device__ __forceinline__ uint4 ln_apply4(uint4 v, float mb, float rden) {
    return make_uint4(ln_apply(v.x, mb, rden), ln_apply(v.y, mb, rden), ln_apply(v.z, mb, rden), ln_apply(v.w, mb, rden));
}
__device__ __forceinline__ void acc_stats(uint32_t v, float piv, float& s, float& q) {
    float a = bf_lo(v) - piv, b = bf_hi(v) - piv;
    s += a + b;
    q = fmaf(a, a, fmaf(b, b, q));
}
__device__ __forceinline__ void ln_x_row(const uint4* __restrict__ src, uint4* __restrict__ dst) {
    uint4 v[8];
#pragma unroll
    for (int i = 0; i < 8; i++) v[i] = __ldg(src + i * 16);
    float s = 0.f;
#pragma unroll
    for (int i = 0; i < 8; i++)
        s += (bf_lo(v[i].x) + bf_hi(v[i].x)) + (bf_lo(v[i].y) + bf_hi(v[i].y)) +
             (bf_lo(v[i].z) + bf_hi(v[i].z)) + (bf_lo(v[i].w) + bf_hi(v[i].w));
#pragma unroll
    for (int o = 8; o > 0; o >>= 1) s += __shfl_xor_sync(0xffffffffu, s, o);
    const float mean = s * (1.0f / D_);
    float q = 0.f, dummy = 0.f;
#pragma unroll
    for (int i = 0; i < 8; i++) {
        acc_stats(v[i].x, mean, dummy, q); acc_stats(v[i].y, mean, dummy, q);
        acc_stats(v[i].z, mean, dummy, q); acc_stats(v[i].w, mean, dummy, q);
    }
#pragma unroll
    for (int o = 8; o > 0; o >>= 1) q += __shfl_xor_sync(0xffffffffu, q, o);
    float mb, rden;
    ln_scalars(mean, q * (1.0f / D_), mb, rden);
#pragma unroll
    for (int i = 0; i < 8; i++) dst[i * 16] = ln_apply4(v[i], mb, rden);
}
__device__ __forceinline__ uint4 ld_ca(const uint4* p) {
    uint4 v;
    asm volatile("ld.global.ca.v4.u32 {%0,%1,%2,%3}, [%4];" : "=r"(v.x), "=r"(v.y), "=r"(v.z), "=r"(v.w) : "l"(p) : "memory");
    return v;
}
__device__ __forceinline__ void ln_z_row(uint4* row  ) {
    float s = 0.f, q = 0.f, piv;
    {
        uint4 a = ld_ca(row), b = ld_ca(row + 32), d = ld_ca(row + 64), e = ld_ca(row + 96);
        piv = __shfl_sync(0xffffffffu, bf_lo(a.x), 0);
        acc_stats(a.x, piv, s, q); acc_stats(a.y, piv, s, q); acc_stats(a.z, piv, s, q); acc_stats(a.w, piv, s, q);
        a = ld_ca(row + 128);
        acc_stats(b.x, piv, s, q); acc_stats(b.y, piv, s, q); acc_stats(b.z, piv, s, q); acc_stats(b.w, piv, s, q);
        b = ld_ca(row + 160);
        acc_stats(d.x, piv, s, q); acc_stats(d.y, piv, s, q); acc_stats(d.z, piv, s, q); acc_stats(d.w, piv, s, q);
        d = ld_ca(row + 192);
        acc_stats(e.x, piv, s, q); acc_stats(e.y, piv, s, q); acc_stats(e.z, piv, s, q); acc_stats(e.w, piv, s, q);
        acc_stats(a.x, piv, s, q); acc_stats(a.y, piv, s, q); acc_stats(a.z, piv, s, q); acc_stats(a.w, piv, s, q);
        acc_stats(b.x, piv, s, q); acc_stats(b.y, piv, s, q); acc_stats(b.z, piv, s, q); acc_stats(b.w, piv, s, q);
        acc_stats(d.x, piv, s, q); acc_stats(d.y, piv, s, q); acc_stats(d.z, piv, s, q); acc_stats(d.w, piv, s, q);
    }
#pragma unroll
    for (int o = 16; o > 0; o >>= 1) {
        s += __shfl_xor_sync(0xffffffffu, s, o);
        q += __shfl_xor_sync(0xffffffffu, q, o);
    }
    const float ms = s * (1.0f / FH_);
    float mb, rden;
    ln_scalars(piv + ms, fmaxf(q * (1.0f / FH_) - ms * ms, 0.f), mb, rden);
#pragma unroll 1
    for (int i = 0; i < 7; i++) row[i * 32] = ln_apply4(ld_ca(row + i * 32), mb, rden);
}

struct Cons {
    uint32_t sbase;
    uint32_t rel;
    uint32_t seq;
    uint32_t par;
    uint32_t st;
    uint32_t stg_par;
    uint32_t wg, warp, lane;
};

__device__ __forceinline__ void c_wait_full(Cons& c, uint32_t idx) {
    mbar_wait(c.sbase + BAR_OFF + 8 * (B_FULL + idx), (c.par >> idx) & 1);
    c.par ^= 1u << idx;
}
__device__ __forceinline__ void c_release(const Cons& c, uint32_t idx) {
    if (c.rel) mbar_arrive_cluster(c.rel + 8 * idx);
}

__device__ __forceinline__ void gemm_main(Cons& c, float (&acc)[128], uint32_t nk) {
    uint32_t g = c.st, prev = 0;
#pragma unroll
    for (int i = 0; i < 128; i++) acc[i] = 0.f;
    pin(acc);
#pragma unroll 1
    for (uint32_t ks = 0; ks < nk; ks++) {
        c_wait_full(c, g);
        uint32_t sa = c.sbase + g * (3 * SLOT);
        uint32_t la = desc_lo_k(sa + c.wg * 8192), lb = desc_lo_mn(sa + SLOT);
        WG_FENCE();
        wgmma_n256(acc, mk_desc(la), mk_desc(lb));
        wgmma_n256(acc, mk_desc(la + 2), mk_desc(lb + 128));
        wgmma_n256(acc, mk_desc(la + 4), mk_desc(lb + 256));
        wgmma_n256(acc, mk_desc(la + 6), mk_desc(lb + 384));
        WG_COMMIT();
        WG_WAIT(1);
        if (ks) c_release(c, prev);
        prev = g;
        g = (g + 1) & 3;
    }
    WG_WAIT(0);
    pin(acc);
    c_release(c, prev);
    c.st = g;
}

__device__ __forceinline__ uint32_t stage_begin(Cons& c) {
    mbar_wait(c.sbase + BAR_OFF + 8 * (B_STG_EMPTY + c.wg), c.stg_par);
    c.stg_par ^= 1;
    const uint32_t lane = threadIdx.x & 31;
    const uint32_t row = c.warp * 16 + (lane & 7) + ((lane >> 3) & 1) * 8;
    return c.sbase + STG_OFF + c.wg * SLOT + row * 128 + (((lane >> 4) ^ (lane & 7)) << 4);
}
__device__ __forceinline__ void stage_put(uint32_t base, int kk, uint32_t r0, uint32_t r1, uint32_t r2, uint32_t r3) {
    stsm4((base ^ ((kk & 3) << 5)) + (kk >> 2) * 8192, r0, r1, r2, r3);
}
__device__ __forceinline__ void stage_end(Cons& c) {
    fence_proxy_async_smem();
    __syncwarp();
    if ((threadIdx.x & 31) == 0) mbar_arrive(c.sbase + BAR_OFF + 8 * (B_STG_FULL + c.wg));
}
__device__ __forceinline__ void stage_out(Cons& c, const uint32_t (&pk)[32]) {
    const uint32_t base = stage_begin(c);
#pragma unroll
    for (int kk = 0; kk < 8; kk++) stage_put(base, kk, pk[4 * kk], pk[4 * kk + 1], pk[4 * kk + 2], pk[4 * kk + 3]);
    stage_end(c);
}

__device__ __forceinline__ void stash_st(uint32_t stash, const uint32_t (&v)[32]) {
#pragma unroll
    for (int i = 0; i < 8; i++)
        asm volatile("st.shared.v4.b32 [%0], {%1,%2,%3,%4};" :: "r"(stash + (i >> 2) * 8192 + (i & 3) * 512),
                     "r"(v[4 * i]), "r"(v[4 * i + 1]), "r"(v[4 * i + 2]), "r"(v[4 * i + 3]) : "memory");
}
__device__ __forceinline__ void stash_ld(uint32_t stash, uint32_t (&v)[32]) {
#pragma unroll
    for (int i = 0; i < 8; i++)
        asm volatile("ld.shared.v4.b32 {%0,%1,%2,%3}, [%4];"
                     : "=r"(v[4 * i]), "=r"(v[4 * i + 1]), "=r"(v[4 * i + 2]), "=r"(v[4 * i + 3])
                     : "r"(stash + (i >> 2) * 8192 + (i & 3) * 512) : "memory");
}
template <int E>
__device__ __forceinline__ void sp_combine(uint32_t (&z)[32], const float (&acc)[128], float b0, float b1) {
#pragma unroll
    for (int i = 0; i < 16; i++) {
        z[2 * i] = pack_bf16(bf_lo(z[2 * i]) * (acc[64 * E + 4 * i] + b0), bf_hi(z[2 * i]) * (acc[64 * E + 4 * i + 1] + b0));
        z[2 * i + 1] = pack_bf16(bf_lo(z[2 * i + 1]) * (acc[64 * E + 4 * i + 2] + b1), bf_hi(z[2 * i + 1]) * (acc[64 * E + 4 * i + 3] + b1));
    }
}
template <int E>
__device__ __forceinline__ void fx_combine(Cons& c, uint32_t (&gt)[32], const float (&acc)[128]) {
    const uint32_t g = c.st;
    c.st = (g + 1) & 3;
    c_wait_full(c, g);
    const uint32_t sa = c.sbase + g * (3 * SLOT);
    const uint32_t row = c.wg * 64 + c.warp * 16 + (c.lane & 7) + ((c.lane >> 3) & 1) * 8;
    const uint32_t pa = sa + SLOT + c.wg * SLOT + (c.warp * 32 + c.lane) * 16;
#pragma unroll
    for (int kk = 0; kk < 4; kk++) {
        uint32_t xr[4];
        ldsm4(sa + row * 128 + (((2 * kk + (c.lane >> 4)) ^ (c.lane & 7)) << 4), xr[0], xr[1], xr[2], xr[3]);
#pragma unroll
        for (int hh = 0; hh < 2; hh++) {
            float4 pv;
            asm volatile("ld.shared.v4.f32 {%0,%1,%2,%3}, [%4];" : "=f"(pv.x), "=f"(pv.y), "=f"(pv.z), "=f"(pv.w)
                         : "r"(pa + (2 * kk + hh) * 2048) : "memory");
            const int ai = 32 * E + 8 * kk + 4 * hh, si = 16 * (E & 1) + 4 * kk + 2 * hh;
            gt[si] = pack_bf16(fmaf(acc[ai] + pv.x, bf_lo(gt[si]), bf_lo(xr[2 * hh])),
                               fmaf(acc[ai + 1] + pv.y, bf_hi(gt[si]), bf_hi(xr[2 * hh])));
            gt[si + 1] = pack_bf16(fmaf(acc[ai + 2] + pv.z, bf_lo(gt[si + 1]), bf_lo(xr[2 * hh + 1])),
                                   fmaf(acc[ai + 3] + pv.w, bf_hi(gt[si + 1]), bf_hi(xr[2 * hh + 1])));
        }
    }
    __syncwarp();
    c_release(c, g);
}

constexpr float SM_C = 0.08838834764831845f * 1.4426950408889634f;

__device__ __forceinline__ void issue_qk(float (&s)[64], const uint32_t (&q)[32], uint32_t kaddr) {
    uint32_t lo = desc_lo_k(kaddr);
    wgmma_n128_rs_init<0>(s, q[0], q[1], q[2], q[3], mk_desc(lo));
#pragma unroll
    for (int kk = 1; kk < 8; kk++)
        wgmma_n128_rs<0>(s, q[4 * kk], q[4 * kk + 1], q[4 * kk + 2], q[4 * kk + 3],
                         mk_desc(lo + (kk >> 2) * (SLOT >> 4) + (kk & 3) * 2), 1);
}
__device__ __forceinline__ void issue_pv(float (&o)[64], const uint32_t (&p)[32], uint32_t vaddr, uint32_t acc) {
    uint32_t lo = desc_lo_mn(vaddr);
#pragma unroll
    for (int kk = 0; kk < 8; kk++)
        wgmma_n128_rs<1>(o, p[4 * kk], p[4 * kk + 1], p[4 * kk + 2], p[4 * kk + 3],
                         mk_desc(lo + (kk >> 2) * (SLOT >> 4) + (kk & 3) * 128), kk ? 1u : acc);
}
__device__ __forceinline__ void row_max(const float (&s)[64], float& m0, float& m1) {
    float a0 = fmaxf(s[0], s[1]), a1 = fmaxf(s[2], s[3]), b0 = fmaxf(s[4], s[5]), b1 = fmaxf(s[6], s[7]);
#pragma unroll
    for (int i = 2; i < 16; i += 2) {
        a0 = fmaxf(a0, fmaxf(s[4 * i], s[4 * i + 1]));
        a1 = fmaxf(a1, fmaxf(s[4 * i + 2], s[4 * i + 3]));
        b0 = fmaxf(b0, fmaxf(s[4 * i + 4], s[4 * i + 5]));
        b1 = fmaxf(b1, fmaxf(s[4 * i + 6], s[4 * i + 7]));
    }
    m0 = fmaxf(a0, b0); m1 = fmaxf(a1, b1);
    m0 = fmaxf(m0, __shfl_xor_sync(0xffffffffu, m0, 1));
    m1 = fmaxf(m1, __shfl_xor_sync(0xffffffffu, m1, 1));
    m0 = fmaxf(m0, __shfl_xor_sync(0xffffffffu, m0, 2));
    m1 = fmaxf(m1, __shfl_xor_sync(0xffffffffu, m1, 2));
}
__device__ __forceinline__ void sub_rows(float (&s)[64], float m0, float m1) {
#pragma unroll
    for (int i = 0; i < 16; i++) { s[4 * i] -= m0; s[4 * i + 1] -= m0; s[4 * i + 2] -= m1; s[4 * i + 3] -= m1; }
}
template <int R> __device__ __forceinline__ void exp_q(float (&s)[64]) {
#pragma unroll
    for (int i = 0; i < 8; i++) {
        const int b = 32 * (R >> 1) + 4 * i + 2 * (R & 1);
        s[b] = ex2(s[b]); s[b + 1] = ex2(s[b + 1]);
    }
}
template <int R> __device__ __forceinline__ void sum_q(const float (&s)[64], float& t) {
#pragma unroll
    for (int i = 0; i < 8; i++) {
        const int b = 32 * (R >> 1) + 4 * i + 2 * (R & 1);
        t += s[b]; t += s[b + 1];
    }
}
template <int R> __device__ __forceinline__ void pack_q(const float (&s)[64], uint32_t (&p)[32]) {
#pragma unroll
    for (int i = 0; i < 8; i++) {
        const int b = 32 * (R >> 1) + 4 * i + 2 * (R & 1);
        asm volatile("cvt.rn.bf16x2.f32 %0, %1, %2;" : "=r"(p[b >> 1]) : "f"(s[b + 1]), "f"(s[b]));
    }
}
__device__ __forceinline__ bool wg_any(uint32_t wg, bool v) {
    uint32_t r;
    asm volatile("{\n.reg .pred p, q;\nsetp.ne.u32 p, %1, 0;\nbarrier.cta.red.or.aligned.pred q, %2, 128, p;\nselp.u32 %0, 1, 0, q;\n}"
                 : "=r"(r) : "r"((uint32_t)v), "r"(3 + wg) : "memory");
    return __any_sync(0xffffffffu, r);
}
__device__ __forceinline__ void pp_sync(uint32_t wg) { asm volatile("bar.sync %0, 256;" :: "r"(1 + wg) : "memory"); }
__device__ __forceinline__ void pp_arrive(uint32_t wg) { asm volatile("bar.arrive %0, 256;" :: "r"(2 - wg) : "memory"); }

__device__ __forceinline__ void attn_store_o(Cons& c, float (&o)[64], float l0, float l1) {
    l0 += __shfl_xor_sync(0xffffffffu, l0, 1); l1 += __shfl_xor_sync(0xffffffffu, l1, 1);
    l0 += __shfl_xor_sync(0xffffffffu, l0, 2); l1 += __shfl_xor_sync(0xffffffffu, l1, 2);
    float r0 = __fdividef(1.0f, l0), r1 = __fdividef(1.0f, l1);
    const uint32_t base = stage_begin(c);
#pragma unroll
    for (int kk = 0; kk < 8; kk++) {
        stage_put(base, kk, pack_bf16(o[8 * kk] * r0, o[8 * kk + 1] * r0), pack_bf16(o[8 * kk + 2] * r1, o[8 * kk + 3] * r1),
                  pack_bf16(o[8 * kk + 4] * r0, o[8 * kk + 5] * r0), pack_bf16(o[8 * kk + 6] * r1, o[8 * kk + 7] * r1));
        if (kk & 1) SCHED_FENCE();
    }
    stage_end(c);
}

__device__ __forceinline__ uint32_t nxt6(uint32_t a) { return a == 5 ? 0 : a + 1; }

constexpr float SM_WINDOW = 20.0f;
constexpr float SM_LIMIT = 1099511627776.0f;
__device__ __forceinline__ bool sm_flagged(uint32_t flag, uint32_t seq) {
    uint32_t f;
    asm volatile("ld.volatile.shared.u32 %0, [%1];" : "=r"(f) : "r"(flag) : "memory");
    return __any_sync(0xffffffffu, f == seq);
}
struct SmState { float m0, m1, l0, l1, t0, t1; uint32_t sub; };
__device__ __forceinline__ void softmax_fix(SmState& st, float (&s)[64], float (&o)[64], uint32_t (&p)[32],
                                            const uint32_t (&q)[32], uint32_t kaddr) {
    WG_FENCE();
    issue_qk(s, q, kaddr);
    WG_COMMIT();
    WG_WAIT(0);
    pin(s);
    float n0, n1;
    row_max(s, n0, n1);
    n0 = fmaxf(n0, st.m0); n1 = fmaxf(n1, st.m1);
    const float al0 = ex2(st.m0 - n0), al1 = ex2(st.m1 - n1);
    st.m0 = n0; st.m1 = n1;
    st.sub = 1;
    st.l0 *= al0; st.l1 *= al1;
#pragma unroll
    for (int i = 0; i < 16; i++) {
        o[4 * i] *= al0; o[4 * i + 1] *= al0; o[4 * i + 2] *= al1; o[4 * i + 3] *= al1;
    }
    sub_rows(s, n0, n1);
    pin(s); SCHED_FENCE();
    exp_q<0>(s); exp_q<1>(s); exp_q<2>(s); exp_q<3>(s);
    pin(s); SCHED_FENCE();
    st.t0 = 0.f; st.t1 = 0.f;
    sum_q<0>(s, st.t0); sum_q<1>(s, st.t1); sum_q<2>(s, st.t0); sum_q<3>(s, st.t1);
    pack_q<0>(s, p); pack_q<1>(s, p); pack_q<2>(s, p); pack_q<3>(s, p);
    pin(s); pin(o); pin(p);
}
__device__ __forceinline__ void attention2(Cons& c, uint32_t (&q)[32], uint32_t stash) {
    float o[64], s[64];
    uint32_t p[32];
    SmState st = {0.f, 0.f, 0.f, 0.f, 0.f, 0.f, 0u};
#pragma unroll
    for (int i = 0; i < 64; i++) { o[i] = 0.f; s[i] = 0.f; }
#pragma unroll
    for (int i = 0; i < 32; i++) p[i] = 0;
    const uint32_t flag = c.sbase + BAR_OFF + 8 * (B_FLAG + c.wg);
    uint32_t ka = g2a(c.st);
    uint32_t va = 0;
    uint32_t a = nxt6(ka);
    c_wait_full(c, 4 + ka);
    pp_sync(c.wg);
    pin(q);
    WG_FENCE();
    issue_qk(s, q, c.sbase + ka * (2 * SLOT));
    WG_COMMIT();
    pp_arrive(c.wg);
    WG_WAIT(0);
    uint32_t t = 0, kprev;
#pragma unroll 1
    while (true) {
        pin(s);
        if ((t & 15) == 0) {
            if (t) {
                __syncwarp();
                attn_store_o(c, o, st.l0, st.l1);
            }
            row_max(s, st.m0, st.m1);
            st.sub = wg_any(c.wg, !(fabsf(st.m0) <= SM_WINDOW && fabsf(st.m1) <= SM_WINDOW));
            if (!st.sub) { st.m0 = 0.f; st.m1 = 0.f; }
            st.l0 = 0.f; st.l1 = 0.f;
        }
        if (st.sub) sub_rows(s, st.m0, st.m1);
        bool done_pv;
#pragma unroll 1
        do {
            pin(s);
            AT(t & 15, 4);
            st.t0 = 0.f; st.t1 = 0.f;
            exp_q<0>(s);
            pin(s); SCHED_FENCE();
            exp_q<1>(s); sum_q<0>(s, st.t0);
            pin(s); SCHED_FENCE();
            exp_q<2>(s); sum_q<1>(s, st.t1);
            pin(s); SCHED_FENCE();
            AT(t & 15, 5);
            WG_WAIT(0);
            pin(o); pin(s);
            AT(t & 15, 6);
            if (t) c_release(c, 4 + va);
            exp_q<3>(s); sum_q<2>(s, st.t0); pack_q<0>(s, p); pack_q<1>(s, p); pack_q<2>(s, p);
            pin(s);
            c_wait_full(c, 4 + a);
            AT(t & 15, 7);
            {
                float u0 = s[34] + s[35], u1 = s[38] + s[39], u2 = s[42] + s[43], u3 = s[46] + s[47];
                u0 += s[50]; u1 += s[51]; u2 += s[54]; u3 += s[55];
                u0 += s[58]; u1 += s[59]; u2 += s[62]; u3 += s[63];
                st.t1 += (u0 + u1) + (u2 + u3);
            }
            if (!(st.t0 <= SM_LIMIT && st.t1 <= SM_LIMIT))
                asm volatile("st.volatile.shared.u32 [%0], %1;" :: "r"(flag), "r"(c.seq) : "memory");
            pack_q<3>(s, p);
            t++;
            AT(t & 15, 0);
            pp_sync(c.wg);
            AT(t & 15, 1);
            pin(o); pin(p); pin(q); pin(s);
            done_pv = false;
            if ((t & 15) == 0) break;
            kprev = ka; ka = a; va = nxt6(a); a = nxt6(va);
            WG_FENCE();
            issue_qk(s, q, c.sbase + ka * (2 * SLOT));
            WG_COMMIT();
            AT(t & 15, 2);
            SCHED_FENCE();
            if (sm_flagged(flag, c.seq)) { WG_WAIT(0); pin(s); break; }
            c_release(c, 4 + kprev);
            st.l0 += st.t0; st.l1 += st.t1;
            c.seq++;
            c_wait_full(c, 4 + va);
            WG_FENCE();
            issue_pv(o, p, c.sbase + va * (2 * SLOT), (t & 15) != 1);
            WG_COMMIT();
            pp_arrive(c.wg);
            AT(t & 15, 3);
            WG_WAIT(1);
            done_pv = true;
        } while (!st.sub);
        if (done_pv) { WG_WAIT(0); pin(o); continue; }
        if ((t & 15) == 0) { kprev = ka; ka = a; }
        if (sm_flagged(flag, c.seq)) softmax_fix(st, s, o, p, q, c.sbase + kprev * (2 * SLOT));
        c_release(c, 4 + kprev);
        st.l0 += st.t0; st.l1 += st.t1;
        c.seq++;
        if (t == 32) break;
        if (t == 16) { va = nxt6(a); a = nxt6(va); stash_ld(stash, q); }
        pin(q);
        WG_FENCE();
        issue_qk(s, q, c.sbase + ka * (2 * SLOT));
        WG_COMMIT();
        c_wait_full(c, 4 + va);
        WG_FENCE();
        issue_pv(o, p, c.sbase + va * (2 * SLOT), (t & 15) != 1);
        WG_COMMIT();
        pp_arrive(c.wg);
        WG_WAIT(0);
        pin(o);
    }
    WG_FENCE();
    issue_pv(o, p, c.sbase + a * (2 * SLOT), 1);
    WG_COMMIT();
    pp_arrive(c.wg);
    WG_WAIT(0);
    pin(o);
    c_release(c, 4 + a);
    attn_store_o(c, o, st.l0, st.l1);
    c.st = a2g(nxt6(a));
}

struct Prod {
    uint32_t sbase, par, st, rank, lane;
};
__device__ __forceinline__ void p_wait_empty(const Prod& p, uint32_t idx) {
    mbar_wait(p.sbase + BAR_OFF + 8 * (B_EMPTY + idx), (p.par >> idx) & 1);
}
__device__ __forceinline__ void p_acquire_g(Prod& p, uint32_t g) {
    uint32_t a0 = (3 * g) >> 1;
    p_wait_empty(p, g);
    p_wait_empty(p, 4 + a0);
    p_wait_empty(p, 5 + a0);
    p.par ^= 1u << g;
}
__device__ __forceinline__ void p_acquire_a(Prod& p, uint32_t a) {
    p_wait_empty(p, 4 + a);
    p_wait_empty(p, (2 * a) / 3);
    p_wait_empty(p, (2 * a + 1) / 3);
    p.par ^= 1u << (4 + a);
}

enum { DEP_NONE = 0, DEP_A_ONE, DEP_A_HEAD, DEP_B_RB };

}

__global__ void __cluster_dims__(2, 1, 1) __launch_bounds__(384, 1)
fused_kernel(const __grid_constant__ Params prm) {
    extern __shared__ __align__(1024) uint8_t smem_raw[];
    const uint32_t sbase = smem_u32(smem_raw);
    const uint32_t lane = threadIdx.x & 31;
    const uint32_t warp_id = __shfl_sync(0xffffffffu, threadIdx.x >> 5, 0);
    uint32_t rank;
    asm volatile("mov.u32 %0, %%cluster_ctarank;" : "=r"(rank));
    const uint32_t pair = blockIdx.x >> 1;
    if (threadIdx.x == 128) TL(2, 2);

    if (threadIdx.x == 0) {
        if (sbase & 1023) die();
        for (int i = 0; i < 10; i++) {
            asm volatile("mbarrier.init.shared::cta.b64 [%0], 1;" :: "r"(sbase + BAR_OFF + 8 * (B_FULL + i)));
            asm volatile("mbarrier.init.shared::cta.b64 [%0], 16;" :: "r"(sbase + BAR_OFF + 8 * (B_EMPTY + i)));
        }
        for (int i = 0; i < 2; i++) {
            asm volatile("mbarrier.init.shared::cta.b64 [%0], 4;" :: "r"(sbase + BAR_OFF + 8 * (B_STG_FULL + i)));
            asm volatile("mbarrier.init.shared::cta.b64 [%0], 1;" :: "r"(sbase + BAR_OFF + 8 * (B_STG_EMPTY + i)));

        }
        asm volatile("fence.mbarrier_init.release.cluster;" ::: "memory");
    }
    __syncwarp();
    asm volatile("barrier.cluster.arrive.relaxed.aligned;" ::: "memory");

    if (warp_id < 4) {
        asm volatile("setmaxnreg.dec.sync.aligned.u32 40;");
        const uint32_t epoch = __ldcg(&g_cnt[C_EXIT]) / (2 * NPAIR) + 1;
        asm volatile("barrier.cluster.wait.acquire.aligned;" ::: "memory");
        if (warp_id == 0) {
            Prod pr{sbase, 0x3ffu, 0, rank, lane};
            uint32_t z2n_mask = 0;
            for (int ii = 0; ii < MAX_ITEMS; ii++) {
                const uint32_t it = prm.sched[pair][ii];
                const uint32_t ty = it_type(it);
                if (ty == T_END) break;
                const uint32_t rb = it_p(it) * 2 + rank, j = it_j(it);
                const int row0 = rb * 128;
                const int nseg = (ty == T_SP || ty == T_FX) ? 2 : 1;
                uint32_t o_mask = 0;
                for (int seg = 0; seg < nseg; seg++) {
                    const CUtensorMap *mA, *mB;
                    uint32_t k0 = 0, k1, chunk, dep, cidx = 0, target = 0;
                    if (ty == T_Z2)       { mA = &prm.maps[M_XN]; mB = &prm.maps[M_WIN]; k1 = 16; chunk = 28 + 4 * j; dep = DEP_A_ONE; cidx = C_XN + rb; target = 64 * epoch; }
                    else if (ty == T_ATT) { mA = &prm.maps[M_XN]; mB = &prm.maps[M_WQ];  k1 = 16; chunk = 4 * j; dep = DEP_A_ONE; cidx = C_XN + rb; target = 64 * epoch; }
                    else if (ty == T_SP && seg == 0) { mA = &prm.maps[M_XN]; mB = &prm.maps[M_WIN]; k1 = 16; chunk = 4 * j; dep = DEP_A_ONE; cidx = C_XN + rb; target = 64 * epoch; }
                    else if (ty == T_SP)  { mA = &prm.maps[M_WSP]; mB = &prm.maps[M_Z2]; k1 = 32; chunk = 4 * j; dep = DEP_B_RB; }
                    else if (ty == T_FX && seg == 0) { mA = &prm.maps[M_H_LD]; mB = &prm.maps[M_WOUT]; k1 = 28; chunk = 4 * j; dep = DEP_A_ONE; cidx = C_H + rb; target = 14 * epoch; }
                    else                  { mA = &prm.maps[M_O_LD]; mB = &prm.maps[M_WO]; k0 = it_k0(it); k1 = it_k1(it); chunk = 4 * j; dep = DEP_A_HEAD; }
                    chunk += 2 * rank;
                    for (uint32_t ks = k0; ks < k1; ks++) {
                        const uint32_t g = pr.st;
                        pr.st = (g + 1) & 3;
                        p_acquire_g(pr, g);
                        const uint32_t bar = sbase + BAR_OFF + 8 * (B_FULL + g);
                        const uint32_t sa = sbase + g * (3 * SLOT);
                        if (dep == DEP_B_RB) {
                            if (lane == 0) { mbar_expect_tx(bar, 3 * SLOT); tma_2d(sa, mA, ks * 64, row0, bar); }
                            poll_mask(&g_cnt[C_Z2N], 16, 128 * epoch, ks >> 1, z2n_mask, lane);
                            if (lane == 0) tma_3d_mc(sa + SLOT + rank * SLOT, mB, ks * 64, chunk, bar);
                        } else {
                            if (lane == 0) { mbar_expect_tx(bar, 3 * SLOT); tma_3d_mc(sa + SLOT + rank * SLOT, mB, ks * 64, chunk, bar); }
                            if (dep == DEP_A_ONE) { if (ks == k0) { if (ii == 0 && lane == 0) TL(2, 0); poll_one(&g_cnt[cidx], target); if (ii == 0 && lane == 0) TL(2, 1); } }
                            else poll_mask(&g_cnt[C_O + rb * 32], 32, 2 * epoch, ks >> 1, o_mask, lane);
                            if (lane == 0) tma_2d(sa, mA, ks * 64, row0, bar);
                        }
                        __syncwarp();
                    }
                }
                if (ty == T_ATT) {
                    uint32_t a = g2a(pr.st);
                    const int kv0 = j * 2 * S_;
                    for (int t = 0; t < 33; t++) {
                        if (t < 32) {
                            p_acquire_a(pr, a);
                            const uint32_t bar = sbase + BAR_OFF + 8 * (B_FULL + 4 + a);
                            if (lane == 0) {
                                mbar_expect_tx(bar, 2 * SLOT);
                                tma_2d_mc(sbase + a * (2 * SLOT) + rank * SLOT, &prm.maps[M_K], rank * 64, kv0 + t * 128, bar);
                            }
                            a = nxt6(a);
                        }
                        if (t > 0) {
                            p_acquire_a(pr, a);
                            const uint32_t bar = sbase + BAR_OFF + 8 * (B_FULL + 4 + a);
                            if (lane == 0) {
                                mbar_expect_tx(bar, 2 * SLOT);
                                tma_3d_mc(sbase + a * (2 * SLOT) + rank * SLOT, &prm.maps[M_V], kv0 + (t - 1) * 128 + rank * 64, 0, bar);
                            }
                            a = nxt6(a);
                        }
                        __syncwarp();
                    }
                    pr.st = a2g(a);
                } else if (ty == T_FX) {
                    for (uint32_t e4 = 0; e4 < 4; e4++) {
                        const uint32_t e = e4 ^ 2;
                        const uint32_t g = pr.st;
                        pr.st = (g + 1) & 3;
                        p_acquire_g(pr, g);
                        const uint32_t bar = sbase + BAR_OFF + 8 * (B_FULL + g);
                        const uint32_t sa = sbase + g * (3 * SLOT);
                        if (lane == 0) { mbar_expect_tx(bar, 3 * SLOT); tma_2d(sa, &prm.maps[M_X], j * 256 + e * 64, row0, bar); }
                        if (e4 == 0) poll_one(&g_cnt[C_PART + rb * 4 + j], 8 * epoch);
                        if (lane == 0) bulk_ld(sa + SLOT, g_part + (size_t)(rb * 4 + j) * 32768 + e * 8192, 2 * SLOT, bar);
                        __syncwarp();
                    }
                }
            }
        } else {
            const uint32_t w = warp_id - 1;
            uint32_t full_par = 0;
            uint32_t nrb = blockIdx.x < 128 ? w : 16;
            auto try_norm = [&]() -> bool {
                uint32_t ok = (int32_t)(ld_relaxed(&g_cnt[C_Z2 + nrb]) - 14 * epoch) >= 0;
                if (!__all_sync(0xffffffffu, ok)) return false;
                fence_acquire();
                fence_proxy_async_all();
                if (lane == 0 && nrb == 2) TL(3, 0);
                ln_z_row(reinterpret_cast<uint4*>(g_z2 + (size_t)(nrb * 128 + blockIdx.x) * FH_) + lane);
                fence_proxy_async_all();
                __syncwarp();
                if (lane == 0) red_release(&g_cnt[C_Z2N + nrb]);
                if (lane == 0 && nrb == 15) TL(3, 1);
                nrb += 3;
                return true;
            };
            for (int ii = 0; ii < MAX_ITEMS && w < 2; ii++) {
                const uint32_t it = prm.sched[pair][ii];
                const uint32_t ty = it_type(it);
                if (ty == T_END) break;
                if (ty == T_FY) continue;
                const uint32_t rb = it_p(it) * 2 + rank, j = it_j(it);
                const CUtensorMap* m = &prm.maps[ty == T_Z2 ? M_Z2 : ty == T_ATT ? M_O_ST : ty == T_SP ? M_H_ST : M_OUT];
                for (uint32_t e = 0; e < 2; e++) {
                    const uint32_t fb = sbase + BAR_OFF + 8 * (B_STG_FULL + w);
                    uint32_t t0 = (uint32_t)clock();
                    while (nrb < 16 && ty != T_Z2 && !__all_sync(0xffffffffu, mbar_test(fb, full_par))) {
                        if (!try_norm()) __nanosleep(256);
                        if ((uint32_t)clock() - t0 > 2000000000u) die();
                    }
                    mbar_wait(fb, full_par);
                    full_par ^= 1;
                    if (lane == 0) {
                        tma_3d_store(m, sbase + STG_OFF + w * SLOT, rb * 128 + w * 64, 4 * j + 2 * (ty == T_ATT ? e : 1 - e));
                        asm volatile("cp.async.bulk.commit_group;" ::: "memory");
                        asm volatile("cp.async.bulk.wait_group.read 0;" ::: "memory");
                        mbar_arrive(sbase + BAR_OFF + 8 * (B_STG_EMPTY + w));
                        if (ty == T_ATT || e == 1) {
                            asm volatile("cp.async.bulk.wait_group 0;" ::: "memory");
                            fence_proxy_async_all();
                            if (ty == T_ATT) red_release(&g_cnt[C_O + rb * 32 + 2 * j + e]);
                            else if (ty == T_Z2) red_release(&g_cnt[C_Z2 + rb]);
                            else if (ty == T_SP) red_release(&g_cnt[C_H + rb]);
                        }
                    }
                    __syncwarp();
                }
            }
            uint32_t t0 = (uint32_t)clock();
            while (nrb < 16) {
                if (!try_norm()) __nanosleep(256);
                if ((uint32_t)clock() - t0 > 2000000000u) die();
            }
        }
    } else {
        asm volatile("setmaxnreg.inc.sync.aligned.u32 232;");
        Cons c;
        c.sbase = sbase; c.par = 0; c.st = 0; c.stg_par = 1; c.seq = 1;
        c.wg = (warp_id >> 2) - 1; c.warp = warp_id & 3; c.lane = lane;
        {
            uint32_t la = sbase + BAR_OFF + 8 * B_EMPTY;
            asm volatile("mapa.shared::cluster.u32 %0, %1, %2;" : "=r"(c.rel) : "r"(la), "r"(lane & 1));
            if (lane >= 2) c.rel = 0;
            asm volatile("" : "+r"(c.rel));
        }
        TLC(62);
        if (blockIdx.x < 128) {
            const uint32_t r0 = blockIdx.x * 16 + (warp_id - 4) * 2 + (lane >> 4);
            ln_x_row(reinterpret_cast<const uint4*>(prm.x + (size_t)r0 * D_) + (lane & 15),
                     reinterpret_cast<uint4*>(g_xn + (size_t)r0 * D_) + (lane & 15));
            TLC(61);
            fence_proxy_async_all();
            TLC(59);
            __syncwarp();
            if (lane == 0) red_release(&g_cnt[C_XN + (blockIdx.x >> 3)]);
        }
        asm volatile("barrier.cluster.wait.acquire.aligned;" ::: "memory");
        if (c.wg == 1) asm volatile("bar.arrive 1, 256;" ::: "memory");
        asm volatile("st.volatile.shared.u32 [%0], 0;" :: "r"(sbase + BAR_OFF + 8 * (B_FLAG + c.wg)) : "memory");

        const uint32_t stash = sbase + STG_OFF + c.wg * SLOT + c.warp * 2048 + lane * 16;
        int ii = 0;
#pragma unroll 1
        for (; ii < MAX_ITEMS; ii++) {
            const uint32_t it = prm.sched[pair][ii];
            const uint32_t ty = it_type(it);
            if (ty == T_END) break;
            const uint32_t rb = it_p(it) * 2 + rank, j = it_j(it);
            TLC(4 * ii);
            uint32_t pk[32];
#pragma unroll
            for (int i = 0; i < 32; i++) pk[i] = 0;
            const uint32_t nkf = it_k1(it) - it_k0(it);
            uint32_t nk = ty == T_FX ? 28 : ty == T_FY ? nkf : 16;
#pragma unroll 1
            for (int seg = 0; seg < 2; seg++) {
                float acc[128];
                gemm_main(c, acc, nk);
                TLC(4 * ii + 1 + 2 * seg);
                if (seg == 1) {
                    uint32_t ph[32];
                    stash_ld(stash, ph);
                    __syncwarp();
                    if (ty == T_SP) {
                        const uint32_t r = rb * 128 + c.wg * 64 + c.warp * 16 + (lane >> 2);
                        const float b0 = __bfloat162float(prm.b_sp[r]), b1 = __bfloat162float(prm.b_sp[r + 8]);
                        sp_combine<1>(ph, acc, b0, b1);
                        stage_out(c, ph);
                        sp_combine<0>(pk, acc, b0, b1);
                        stage_out(c, pk);
                    } else {
                        fx_combine<2>(c, ph, acc);
                        fx_combine<3>(c, ph, acc);
                        stage_out(c, ph);
                        fx_combine<0>(c, pk, acc);
                        fx_combine<1>(c, pk, acc);
                        stage_out(c, pk);
                    }
                    break;
                }
                if (ty == T_FY) {
                    float4* dst = reinterpret_cast<float4*>(g_part + (size_t)(rb * 4 + j) * 32768) + c.wg * 1024 + (threadIdx.x & 127);
#pragma unroll
                    for (int i = 0; i < 32; i++)
                        __stcg(dst + (i >> 3) * 2048 + (i & 7) * 128, make_float4(acc[4 * i], acc[4 * i + 1], acc[4 * i + 2], acc[4 * i + 3]));
                    fence_proxy_async_all();
                    __syncwarp();
                    if (lane == 0) red_release(&g_cnt[C_PART + rb * 4 + j]);
                    break;
                }
                if (ty == T_ATT) {
                    uint32_t q[32];
#pragma unroll
                    for (int i = 0; i < 32; i++) q[i] = pack_bf16(acc[64 + 2 * i] * SM_C, acc[64 + 2 * i + 1] * SM_C);
                    mbar_wait(sbase + BAR_OFF + 8 * (B_STG_EMPTY + c.wg), c.stg_par);
                    stash_st(stash, q);
#pragma unroll
                    for (int i = 0; i < 32; i++) q[i] = pack_bf16(acc[2 * i] * SM_C, acc[2 * i + 1] * SM_C);
                    TLC(4 * ii + 2);
                    attention2(c, q, stash);
                    break;
                }
#pragma unroll
                for (int e = 1; e >= 0; e--) {
                    if (ty == T_FX) {
#pragma unroll
                        for (int i = 0; i < 32; i++) pk[i] = pack_bf16(silu(acc[64 * e + 2 * i]), silu(acc[64 * e + 2 * i + 1]));
                    } else {
#pragma unroll
                        for (int i = 0; i < 32; i++) pk[i] = pack_bf16(gelu_tanh(acc[64 * e + 2 * i]), gelu_tanh(acc[64 * e + 2 * i + 1]));
                    }
                    if (ty == T_Z2) stage_out(c, pk);
                    else if (e == 1) {
                        mbar_wait(sbase + BAR_OFF + 8 * (B_STG_EMPTY + c.wg), c.stg_par);
                        stash_st(stash, pk);
                    }
                }
                TLC(4 * ii + 2);
                if (ty == T_Z2) break;
                nk = ty == T_SP ? 32 : nkf;
            }
        }
        TLC(4 * ii);
    }
    __syncwarp();
    asm volatile("barrier.cluster.arrive.relaxed.aligned;" ::: "memory");
    asm volatile("barrier.cluster.wait.aligned;" ::: "memory");
    if (threadIdx.x == 0) { TL(2, 3); atomicAdd(&g_cnt[C_EXIT], 1u); }
}

typedef CUresult (*EncodeFn)(CUtensorMap*, CUtensorMapDataType, cuuint32_t, void*, const cuuint64_t*, const cuuint64_t*,
                             const cuuint32_t*, const cuuint32_t*, CUtensorMapInterleave, CUtensorMapSwizzle,
                             CUtensorMapL2promotion, CUtensorMapFloatOOBfill);

static void make_2d(EncodeFn f, CUtensorMap* m, const void* p, uint64_t rows, uint64_t cols) {
    cuuint64_t dims[2] = {cols, rows};
    cuuint64_t strides[1] = {cols * 2};
    cuuint32_t box[2] = {64, 128}, es[2] = {1, 1};
    f(m, CU_TENSOR_MAP_DATA_TYPE_BFLOAT16, 2, const_cast<void*>(p), dims, strides, box, es, CU_TENSOR_MAP_INTERLEAVE_NONE,
      CU_TENSOR_MAP_SWIZZLE_128B, CU_TENSOR_MAP_L2_PROMOTION_L2_256B, CU_TENSOR_MAP_FLOAT_OOB_FILL_NONE);
}
static void make_3d(EncodeFn f, CUtensorMap* m, const void* p, uint64_t rows, uint64_t cols) {
    cuuint64_t dims[3] = {64, rows, cols / 64};
    cuuint64_t strides[2] = {cols * 2, 128};
    cuuint32_t box[3] = {64, 64, 2}, es[3] = {1, 1, 1};
    f(m, CU_TENSOR_MAP_DATA_TYPE_BFLOAT16, 3, const_cast<void*>(p), dims, strides, box, es, CU_TENSOR_MAP_INTERLEAVE_NONE,
      CU_TENSOR_MAP_SWIZZLE_128B, CU_TENSOR_MAP_L2_PROMOTION_L2_256B, CU_TENSOR_MAP_FLOAT_OOB_FILL_NONE);
}

#define KS_LATE 54
#define KS_NORM 44
static void build_schedule(uint32_t (*sched)[MAX_ITEMS]) {
    int n[NPAIR];
    for (int i = 0; i < NPAIR; i++) { n[i] = 0; for (int k = 0; k < MAX_ITEMS; k++) sched[i][k] = T_END; }
    auto push = [&](int pr, uint32_t it) { sched[pr][n[pr]++] = it; };
    int z = 0;
    for (int pr = 0; pr < 8; pr++) { push(pr, mk_item(T_Z2, z / 7, z % 7)); z++; }
    for (int r = 0; r < 3; r++)
        for (int pr = 50; pr < 66; pr++) { push(pr, mk_item(T_Z2, z / 7, z % 7)); z++; }
    for (int pr = 0; pr < 64; pr++) push(pr, mk_item(T_ATT, pr % 8, pr / 8));
    for (int r = 0; r < 3; r++)
        for (int pr = 64; pr < 66; pr++) push(pr, mk_item(T_SP, 6 + (pr - 64), r));
    int pr_sp = 0;
    for (int j = 0; j < 7; j++)
        for (int p = 0; p < 8; p++)
            if (!(p >= 6 && j < 3)) push(pr_sp++, mk_item(T_SP, p, j));
    for (int pr = 0; pr < 64; pr++) push(pr, mk_item(T_ATT, pr % 8, 15 - pr / 8));
    for (int t = 0; t < 32; t++) {
        int p = t < 8 ? 6 + (t & 1) : (t - 8) % 6, nn = t < 8 ? t >> 1 : (t - 8) / 6;
        int ks = t < 8 ? KS_LATE : KS_NORM;
        push(t, mk_item(T_FX, p, nn, ks, 64));
        push(t + 32, mk_item(T_FY, p, nn, 0, ks));
    }
}

extern "C" void kernel_launch(void* const* d_in, const int* in_sizes, int n_in, void* d_out, int out_size) {
    (void)in_sizes; (void)n_in; (void)out_size;
    static EncodeFn enc = nullptr;
    static void *p_xn, *p_z2, *p_o, *p_h;
    if (!enc) {
        void* fn = nullptr;
        cudaDriverEntryPointQueryResult qr;
        cudaGetDriverEntryPoint("cuTensorMapEncodeTiled", &fn, cudaEnableDefault, &qr);
        enc = (EncodeFn)fn;
        cudaFuncSetAttribute(fused_kernel, cudaFuncAttributeMaxDynamicSharedMemorySize, SMEM_BYTES);
        cudaGetSymbolAddress(&p_xn, g_xn);
        cudaGetSymbolAddress(&p_z2, g_z2);
        cudaGetSymbolAddress(&p_o, g_o);
        cudaGetSymbolAddress(&p_h, g_h);
    }
    Params prm;
    make_2d(enc, &prm.maps[M_XN], p_xn, S_, D_);
    make_2d(enc, &prm.maps[M_WSP], d_in[7], S_, S_);
    make_2d(enc, &prm.maps[M_O_LD], p_o, S_, H_ * DH_);
    make_2d(enc, &prm.maps[M_H_LD], p_h, S_, FH_);
    make_2d(enc, &prm.maps[M_X], d_in[0], S_, D_);
    make_2d(enc, &prm.maps[M_K], d_in[1], (uint64_t)H_ * S_, DH_);
    make_3d(enc, &prm.maps[M_WQ], d_in[3], D_, H_ * DH_);
    make_3d(enc, &prm.maps[M_WIN], d_in[6], D_, F_);
    make_3d(enc, &prm.maps[M_WO], d_in[4], H_ * DH_, D_);
    make_3d(enc, &prm.maps[M_WOUT], d_in[9], FH_, D_);
    make_3d(enc, &prm.maps[M_Z2], p_z2, S_, FH_);
    make_3d(enc, &prm.maps[M_V], d_in[2], (uint64_t)H_ * S_, DH_);
    make_3d(enc, &prm.maps[M_O_ST], p_o, S_, H_ * DH_);
    make_3d(enc, &prm.maps[M_H_ST], p_h, S_, FH_);
    make_3d(enc, &prm.maps[M_OUT], d_out, S_, D_);
    prm.x = (const __nv_bfloat16*)d_in[0];
    prm.b_sp = (const __nv_bfloat16*)d_in[8];
    build_schedule(prm.sched);
    fused_kernel<<<2 * NPAIR, 384, SMEM_BYTES>>>(prm);
}
```

```cpp
#include <cuda_runtime.h>
#include <cuda_bf16.h>
#include <cuda.h>
#include <stdint.h>

namespace {

constexpr int S_ = 2048, D_ = 1024, H_ = 32, DH_ = 128, FH_ = 1792, F_ = 3584;
constexpr int NPAIR = 66;
constexpr int MAX_ITEMS = 10;
constexpr uint32_t NRAW = 2;

constexpr uint32_t SLOT = 16384;
constexpr uint32_t RING_BYTES = 12 * SLOT;
constexpr uint32_t STG_OFF = RING_BYTES;
constexpr uint32_t BAR_OFF = STG_OFF + 2 * SLOT;
constexpr uint32_t SMEM_BYTES = BAR_OFF + 256;
constexpr uint32_t B_FULL = 0;
constexpr uint32_t B_EMPTY = 10;
constexpr uint32_t B_STG_FULL = 20;
constexpr uint32_t B_STG_EMPTY = 22;
constexpr uint32_t B_FLAG = 24;
constexpr uint32_t B_NEXT = 26;
constexpr uint32_t B_EPOCH = 27;
constexpr uint32_t B_EPOCH_BAR = 28;
constexpr uint32_t B_GATE = 29;

enum : uint32_t { T_END = 0, T_Z2 = 1, T_ATT = 2, T_SP = 3, T_FX = 4, T_FY = 5, T_FH = 6 };
__host__ __device__ constexpr uint32_t mk_item(uint32_t t, uint32_t p, uint32_t j, uint32_t k0 = 0, uint32_t k1 = 0,
                                               uint32_t kh = 0) {
    return t | (p << 3) | (j << 6) | (k0 << 10) | (k1 << 17) | (kh << 24);
}
__device__ __forceinline__ uint32_t it_type(uint32_t it) { return it & 7; }
__device__ __forceinline__ uint32_t it_p(uint32_t it) { return (it >> 3) & 7; }
__device__ __forceinline__ uint32_t it_j(uint32_t it) { return (it >> 6) & 15; }
__device__ __forceinline__ uint32_t it_k0(uint32_t it) { return (it >> 10) & 127; }
__device__ __forceinline__ uint32_t it_k1(uint32_t it) { return (it >> 17) & 127; }
__device__ __forceinline__ uint32_t it_kh(uint32_t it) { return it >> 24; }

enum { M_XN = 0, M_XRAW, M_WSP, M_O_LD, M_H_LD, M_K,
       M_O_LD64,
       M_X, M_WQ, M_WIN, M_WO, M_WOUT, M_Z2, M_V, M_O_ST, M_H_ST, M_HELP, M_GATE, M_OUT,
       M_COUNT };

struct Params {
    CUtensorMap maps[M_COUNT];
    const __nv_bfloat16* x;
    const __nv_bfloat16* b_sp;
    uint32_t zero;
    uint32_t sched[NPAIR][MAX_ITEMS];
};

__device__ __align__(1024) __nv_bfloat16 g_xn[S_ * D_];
__device__ __align__(1024) __nv_bfloat16 g_z2[S_ * FH_];
__device__ __align__(1024) __nv_bfloat16 g_o[S_ * H_ * DH_];
__device__ __align__(1024) __nv_bfloat16 g_h[S_ * FH_];
__device__ __align__(1024) uint32_t g_part[S_ * D_ / 2];
__device__ __align__(1024) __nv_bfloat16 g_gate[S_ * D_];
__device__ __align__(1024) __nv_bfloat16 g_help[S_ * 256];
constexpr int CS = 32;
constexpr int C_XN = 0;
constexpr int C_Z2 = 16 * CS;
constexpr int C_Z2N = 32 * CS;
constexpr int C_H = 48 * CS;
constexpr int C_PART = 64 * CS;
constexpr int C_GATE = 192 * CS;
constexpr int C_O = 256 * CS;
constexpr int C_HELP = 272 * CS;
constexpr int C_EXIT = 288 * CS;
constexpr int C_STAT = 289 * CS;
__device__ __align__(65536) uint32_t g_cnt[C_STAT + 2 * S_];
#define g_stat (reinterpret_cast<unsigned long long*>(g_cnt + C_STAT))

__device__ __forceinline__ uint32_t smem_u32(const void* p) { return (uint32_t)__cvta_generic_to_shared(p); }

#define UNLIKELY(x) __builtin_expect(!!(x), 0)
__device__ __forceinline__ void die() { asm volatile("trap;\nexit;"); __builtin_unreachable(); }

__device__ __forceinline__ uint32_t mbar_try(uint32_t bar, uint32_t parity) {
    uint32_t ok;
    asm volatile("{\n.reg .pred p;\nmbarrier.try_wait.parity.shared::cta.b64 p, [%1], %2;\nselp.u32 %0, 1, 0, p;\n}"
                 : "=r"(ok) : "r"(bar), "r"(parity) : "memory");
    return ok;
}
__device__ __forceinline__ uint32_t lane_id() { uint32_t l; asm volatile("mov.u32 %0, %%laneid;" : "=r"(l)); return l; }
__device__ __forceinline__ bool elect_one() {
    uint32_t p;
    asm volatile("{\n.reg .pred p;\nelect.sync _|p, 0xffffffff;\nselp.u32 %0, 1, 0, p;\n}" : "=r"(p));
    return p;
}
__device__ __forceinline__ uint32_t mbar_test(uint32_t bar, uint32_t parity) {
    uint32_t ok;
    asm volatile("{\n.reg .pred p;\nmbarrier.test_wait.parity.shared::cta.b64 p, [%1], %2;\nselp.u32 %0, 1, 0, p;\n}"
                 : "=r"(ok) : "r"(bar), "r"(parity) : "memory");
    return ok;
}
template <int TAG = 0>
__device__ __forceinline__ void mbar_wait(uint32_t bar, uint32_t parity) {
    if (UNLIKELY(!mbar_try(bar, parity))) {
        uint32_t t0 = (uint32_t)clock();
        while (!mbar_try(bar, parity)) {
            if ((uint32_t)clock() - t0 > 2000000000u) { if (TAG) asm volatile("pmevent %0;" :: "n"(TAG)); die(); }
        }
    }
}
__device__ __forceinline__ uint32_t get_epoch(uint32_t sbase) {
    uint32_t v;
    mbar_wait(sbase + BAR_OFF + 8 * B_EPOCH_BAR, 0);
    asm volatile("ld.volatile.shared.u32 %0, [%1];" : "=r"(v) : "r"(sbase + BAR_OFF + 8 * B_EPOCH) : "memory");
    return __shfl_sync(0xffffffffu, v, 0);
}
__device__ __forceinline__ void mbar_arrive(uint32_t bar) {
    asm volatile("mbarrier.arrive.shared::cta.b64 _, [%0];" :: "r"(bar) : "memory");
}
__device__ __forceinline__ void mbar_arrive_cluster_if(uint32_t cluster_addr, uint32_t on) {
    asm volatile("{\n.reg .pred p;\nsetp.ne.u32 p, %1, 0;\n@p mbarrier.arrive.shared::cluster.b64 _, [%0];\n}"
                 :: "r"(cluster_addr), "r"(on) : "memory");
}
__device__ __forceinline__ void mbar_arrive_cluster_n_if(uint32_t cluster_addr, uint32_t on, uint32_t n) {
    asm volatile("{\n.reg .pred p;\nsetp.ne.u32 p, %1, 0;\n@p mbarrier.arrive.shared::cluster.b64 _, [%0], %2;\n}"
                 :: "r"(cluster_addr), "r"(on), "r"(n) : "memory");
}
__device__ __forceinline__ void mbar_arrive_lane0(uint32_t bar) {
    asm volatile("{\n.reg .pred p;\nsetp.eq.u32 p, %1, 0;\n@p mbarrier.arrive.shared::cta.b64 _, [%0];\n}"
                 :: "r"(bar), "r"(lane_id()) : "memory");
}
__device__ __forceinline__ void mbar_expect_tx(uint32_t bar, uint32_t bytes) {
    asm volatile("mbarrier.arrive.expect_tx.shared::cta.b64 _, [%0], %1;" :: "r"(bar), "r"(bytes) : "memory");
}
__device__ __forceinline__ void tma_2d(uint32_t dst, const CUtensorMap* m, int c0, int c1, uint32_t bar) {
    asm volatile("cp.async.bulk.tensor.2d.shared::cluster.global.mbarrier::complete_tx::bytes [%0], [%1, {%3, %4}], [%2];"
                 :: "r"(dst), "l"(m), "r"(bar), "r"(c0), "r"(c1) : "memory");
}
__device__ __forceinline__ void tma_2d_mc(uint32_t dst, const CUtensorMap* m, int c0, int c1, uint32_t bar) {
    asm volatile("cp.async.bulk.tensor.2d.shared::cluster.global.mbarrier::complete_tx::bytes.multicast::cluster [%0], [%1, {%3, %4}], [%2], %5;"
                 :: "r"(dst), "l"(m), "r"(bar), "r"(c0), "r"(c1), "h"((uint16_t)3) : "memory");
}
__device__ __forceinline__ void tma_3d(uint32_t dst, const CUtensorMap* m, int c1, int c2, uint32_t bar) {
    asm volatile("cp.async.bulk.tensor.3d.shared::cluster.global.mbarrier::complete_tx::bytes [%0], [%1, {%3, %4, %5}], [%2];"
                 :: "r"(dst), "l"(m), "r"(bar), "r"(0), "r"(c1), "r"(c2) : "memory");
}
__device__ __forceinline__ void tma_3d_mc(uint32_t dst, const CUtensorMap* m, int c1, int c2, uint32_t bar) {
    asm volatile("cp.async.bulk.tensor.3d.shared::cluster.global.mbarrier::complete_tx::bytes.multicast::cluster [%0], [%1, {%3, %4, %5}], [%2], %6;"
                 :: "r"(dst), "l"(m), "r"(bar), "r"(0), "r"(c1), "r"(c2), "h"((uint16_t)3) : "memory");
}
__device__ __forceinline__ void bulk_ld(uint32_t dst, const void* src, uint32_t bytes, uint32_t bar) {
    asm volatile("cp.async.bulk.shared::cluster.global.mbarrier::complete_tx::bytes [%0], [%1], %2, [%3];"
                 :: "r"(dst), "l"(src), "r"(bytes), "r"(bar) : "memory");
}
__device__ __forceinline__ void tma_3d_store(const CUtensorMap* m, uint32_t src, int c1, int c2) {
    asm volatile("cp.async.bulk.tensor.3d.global.shared::cta.bulk_group [%0, {%2, %3, %4}], [%1];"
                 :: "l"(m), "r"(src), "r"(0), "r"(c1), "r"(c2) : "memory");
}
__device__ __forceinline__ uint32_t ld_relaxed(const uint32_t* p) {
    uint32_t v;
    asm volatile("ld.relaxed.gpu.global.u32 %0, [%1];" : "=r"(v) : "l"(p) : "memory");
    return v;
}
__device__ __forceinline__ void fence_acquire() { asm volatile("fence.acquire.gpu;" ::: "memory"); }
__device__ __forceinline__ void red_release(uint32_t* p) {
    asm volatile("red.release.gpu.global.add.u32 [%0], 1;" :: "l"(p) : "memory");
}
__device__ __forceinline__ void fence_proxy_async_all() { asm volatile("fence.proxy.async.global;" ::: "memory"); }
__device__ __forceinline__ void fence_proxy_async_smem() { asm volatile("fence.proxy.async.shared::cta;" ::: "memory"); }

__device__ __forceinline__ void poll_mask(const uint32_t* base, uint32_t n, uint32_t stride, uint32_t target, uint32_t need,
                                          uint32_t& mask, uint32_t lane) {
    if ((mask >> need) & 1) return;
    uint32_t t0 = (uint32_t)clock();
    while (true) {
        uint32_t ok = 0;
        if (lane < n) ok = (int32_t)(ld_relaxed(base + lane * stride) - target) >= 0;
        mask = __ballot_sync(0xffffffffu, ok);
        if ((mask >> need) & 1) break;
        __nanosleep(64);
        if ((uint32_t)clock() - t0 > 2000000000u) die();
    }
    fence_acquire();
    __syncwarp();
    fence_proxy_async_all();
}
__device__ __forceinline__ void poll_one(const uint32_t* p, uint32_t target) {
    uint32_t t0 = (uint32_t)clock();
    while (!__all_sync(0xffffffffu, (int32_t)(ld_relaxed(p) - target) >= 0)) {
        __nanosleep(32);
        if ((uint32_t)clock() - t0 > 2000000000u) die();
    }
    fence_acquire();
    fence_proxy_async_all();
}

#define WG_FENCE() asm volatile("wgmma.fence.sync.aligned;" ::: "memory")
#define WG_COMMIT() asm volatile("wgmma.commit_group.sync.aligned;" ::: "memory")
#define WG_WAIT(n) asm volatile("wgmma.wait_group.sync.aligned %0;" :: "n"(n) : "memory")

#define SCHED_FENCE() asm volatile("pmevent 0;" ::: "memory")

constexpr uint32_t DESC_HI = (1024u >> 4) | (1u << 30);
constexpr uint32_t DESC_MN = ((8192u >> 4) - 1) << 16;

#define R8(d, i) "+f"(d[i]), "+f"(d[i + 1]), "+f"(d[i + 2]), "+f"(d[i + 3]), "+f"(d[i + 4]), "+f"(d[i + 5]), "+f"(d[i + 6]), "+f"(d[i + 7])

template <int N> __device__ __forceinline__ void pin(float (&d)[N]) {
#pragma unroll
    for (int i = 0; i < N; i++) asm volatile("" : "+f"(d[i]) :: "memory");
}
template <int N> __device__ __forceinline__ void pin(uint32_t (&d)[N]) {
#pragma unroll
    for (int i = 0; i < N; i++) asm volatile("" : "+r"(d[i]) :: "memory");
}

#define W8(d, i) "=f"(d[i]), "=f"(d[i + 1]), "=f"(d[i + 2]), "=f"(d[i + 3]), "=f"(d[i + 4]), "=f"(d[i + 5]), "=f"(d[i + 6]), "=f"(d[i + 7])
#define REGS64 "%0,%1,%2,%3,%4,%5,%6,%7,%8,%9,%10,%11,%12,%13,%14,%15," \
        "%16,%17,%18,%19,%20,%21,%22,%23,%24,%25,%26,%27,%28,%29,%30,%31," \
        "%32,%33,%34,%35,%36,%37,%38,%39,%40,%41,%42,%43,%44,%45,%46,%47," \
        "%48,%49,%50,%51,%52,%53,%54,%55,%56,%57,%58,%59,%60,%61,%62,%63"
#define REGS128 REGS64 "," \
        "%64,%65,%66,%67,%68,%69,%70,%71,%72,%73,%74,%75,%76,%77,%78,%79," \
        "%80,%81,%82,%83,%84,%85,%86,%87,%88,%89,%90,%91,%92,%93,%94,%95," \
        "%96,%97,%98,%99,%100,%101,%102,%103,%104,%105,%106,%107,%108,%109,%110,%111," \
        "%112,%113,%114,%115,%116,%117,%118,%119,%120,%121,%122,%123,%124,%125,%126,%127"

__device__ __forceinline__ void wgmma_n256(float (&d)[128], uint64_t da, uint64_t db) {
    asm volatile("wgmma.mma_async.sync.aligned.m64n256k16.f32.bf16.bf16 {" REGS128 "}, %128, %129, 1, 1, 1, 0, 1;\n"
        : R8(d, 0), R8(d, 8), R8(d, 16), R8(d, 24), R8(d, 32), R8(d, 40), R8(d, 48), R8(d, 56),
          R8(d, 64), R8(d, 72), R8(d, 80), R8(d, 88), R8(d, 96), R8(d, 104), R8(d, 112), R8(d, 120)
        : "l"(da), "l"(db));
}
__device__ __forceinline__ void wgmma_n256_init(float (&d)[128], uint64_t da, uint64_t db) {
    asm volatile("wgmma.mma_async.sync.aligned.m64n256k16.f32.bf16.bf16 {" REGS128 "}, %128, %129, 0, 1, 1, 0, 1;\n"
        : W8(d, 0), W8(d, 8), W8(d, 16), W8(d, 24), W8(d, 32), W8(d, 40), W8(d, 48), W8(d, 56),
          W8(d, 64), W8(d, 72), W8(d, 80), W8(d, 88), W8(d, 96), W8(d, 104), W8(d, 112), W8(d, 120)
        : "l"(da), "l"(db));
}
template <int TB>
__device__ __forceinline__ void wgmma_n128_rs(float (&d)[64], uint32_t a0, uint32_t a1, uint32_t a2, uint32_t a3,
                                              uint64_t db, uint32_t acc) {
    asm volatile("{\n.reg .pred p;\nsetp.ne.b32 p, %69, 0;\n"
        "wgmma.mma_async.sync.aligned.m64n128k16.f32.bf16.bf16 {" REGS64 "}, {%64,%65,%66,%67}, %68, p, 1, 1, %70;\n}\n"
        : R8(d, 0), R8(d, 8), R8(d, 16), R8(d, 24), R8(d, 32), R8(d, 40), R8(d, 48), R8(d, 56)
        : "r"(a0), "r"(a1), "r"(a2), "r"(a3), "l"(db), "r"(acc), "n"(TB));
}
template <int TB>
__device__ __forceinline__ void wgmma_n128_rs_init(float (&d)[64], uint32_t a0, uint32_t a1, uint32_t a2, uint32_t a3,
                                                   uint64_t db) {
    asm volatile("wgmma.mma_async.sync.aligned.m64n128k16.f32.bf16.bf16 {" REGS64 "}, {%64,%65,%66,%67}, %68, 0, 1, 1, %69;\n"
        : W8(d, 0), W8(d, 8), W8(d, 16), W8(d, 24), W8(d, 32), W8(d, 40), W8(d, 48), W8(d, 56)
        : "r"(a0), "r"(a1), "r"(a2), "r"(a3), "l"(db), "n"(TB));
}

__device__ __forceinline__ uint32_t pack_bf16(float lo, float hi) {
    uint32_t r;
    asm("cvt.rn.bf16x2.f32 %0, %1, %2;" : "=r"(r) : "f"(hi), "f"(lo));
    return r;
}
__device__ __forceinline__ float bf_lo(uint32_t v) { return __uint_as_float(v << 16); }
__device__ __forceinline__ float bf_hi(uint32_t v) { return __uint_as_float(v & 0xffff0000u); }
__device__ __forceinline__ float bf_round(float f) { return __bfloat162float(__float2bfloat16_rn(f)); }
__device__ __forceinline__ float ex2(float x) { float y; asm("ex2.approx.ftz.f32 %0, %1;" : "=f"(y) : "f"(x)); return y; }
__device__ __forceinline__ float tanh_fast(float x) { float y; asm("tanh.approx.f32 %0, %1;" : "=f"(y) : "f"(x)); return y; }
__device__ __forceinline__ uint32_t bf2_mul(uint32_t a, uint32_t b) {
    uint32_t d;
    asm("mul.rn.bf16x2 %0, %1, %2;" : "=r"(d) : "r"(a), "r"(b));
    return d;
}
__device__ __forceinline__ uint32_t bf2_add(uint32_t a, uint32_t b) {
    uint32_t d;
    asm("add.rn.bf16x2 %0, %1, %2;" : "=r"(d) : "r"(a), "r"(b));
    return d;
}
__device__ __forceinline__ uint32_t bf2_fma(uint32_t a, uint32_t b, uint32_t c) {
    uint32_t d;
    asm("fma.rn.bf16x2 %0, %1, %2, %3;" : "=r"(d) : "r"(a), "r"(b), "r"(c));
    return d;
}
__device__ __forceinline__ void stsm4(uint32_t addr, uint32_t r0, uint32_t r1, uint32_t r2, uint32_t r3) {
    asm volatile("stmatrix.sync.aligned.m8n8.x4.shared.b16 [%0], {%1,%2,%3,%4};"
                 :: "r"(addr), "r"(r0), "r"(r1), "r"(r2), "r"(r3) : "memory");
}
__device__ __forceinline__ void ldsm4(uint32_t addr, uint32_t& r0, uint32_t& r1, uint32_t& r2, uint32_t& r3) {
    asm volatile("ldmatrix.sync.aligned.m8n8.x4.shared.b16 {%0,%1,%2,%3}, [%4];"
                 : "=r"(r0), "=r"(r1), "=r"(r2), "=r"(r3) : "r"(addr) : "memory");
}

__device__ __forceinline__ uint32_t g2a(uint32_t g) { return (3 * g + 1) >> 1; }
__device__ __forceinline__ uint32_t a2g(uint32_t a) { return ((2 * a + 2) / 3) & 3; }

__device__ __forceinline__ uint32_t ln_x_apply(uint32_t w, uint32_t m2, float r) {
    const uint32_t d = bf2_add(w, m2);
    return pack_bf16(bf_lo(d) * r, bf_hi(d) * r);
}
__device__ __forceinline__ void ln_x_row(const uint4 (&v)[8], uint4* __restrict__ dst, unsigned long long* stat, uint32_t tag) {
    float s0 = 0.f, s1 = 0.f, q0 = 0.f, q1 = 0.f;
#pragma unroll
    for (int i = 0; i < 8; i++) {
        const uint32_t w[4] = {v[i].x, v[i].y, v[i].z, v[i].w};
#pragma unroll
        for (int k = 0; k < 4; k++) {
            const float a = bf_lo(w[k]), b = bf_hi(w[k]);
            s0 += a; s1 += b;
            q0 = fmaf(a, a, q0); q1 = fmaf(b, b, q1);
        }
    }
    float s = s0 + s1, q = q0 + q1;
#pragma unroll
    for (int o = 8; o > 0; o >>= 1) {
        s += __shfl_xor_sync(0xffffffffu, s, o);
        q += __shfl_xor_sync(0xffffffffu, q, o);
    }
    const float mean = s * (1.0f / D_);
    const float var = fmaxf(q * (1.0f / D_) - mean * mean, 0.f);
    float sq;
    asm("sqrt.approx.f32 %0, %1;" : "=f"(sq) : "f"(bf_round(bf_round(var) + 1e-5f)));
    const float r = __fdividef(1.0f, bf_round(sq));
    const uint32_t m2 = pack_bf16(-mean, -mean);
    if (stat)
        asm volatile("st.relaxed.gpu.global.b64 [%0], %1;" :: "l"(stat),
                     "l"(((unsigned long long)((m2 & 0xffff0000u) | tag) << 32) | __float_as_uint(r)) : "memory");
#pragma unroll
    for (int i = 0; i < 8; i++)
        dst[i * 16] = make_uint4(ln_x_apply(v[i].x, m2, r), ln_x_apply(v[i].y, m2, r), ln_x_apply(v[i].z, m2, r), ln_x_apply(v[i].w, m2, r));
}
__device__ __forceinline__ uint4 ld_l2(const uint4* p) {
    uint4 v;
    asm volatile("ld.relaxed.gpu.global.v4.u32 {%0,%1,%2,%3}, [%4];" : "=r"(v.x), "=r"(v.y), "=r"(v.z), "=r"(v.w) : "l"(p) : "memory");
    return v;
}
__device__ __forceinline__ void z_stats(const uint4& v, float& s, float& q) {
    const uint32_t w[4] = {v.x, v.y, v.z, v.w};
#pragma unroll
    for (int k = 0; k < 4; k++) {
        const float a = bf_lo(w[k]), b = bf_hi(w[k]);
        s += a; s += b;
        q = fmaf(a, a, q); q = fmaf(b, b, q);
    }
}
__device__ __forceinline__ uint4 z_apply(const uint4& v, uint32_t r2, uint32_t m2) {
    return make_uint4(bf2_fma(v.x, r2, m2), bf2_fma(v.y, r2, m2), bf2_fma(v.z, r2, m2), bf2_fma(v.w, r2, m2));
}
#define Z_NAP() do { asm volatile("" : "+f"(s), "+f"(q)); SCHED_FENCE(); if (nap) __nanosleep(nap); } while (0)
__device__ __forceinline__ void ln_z_row(uint4* row  , uint32_t nap) {
    float s = 0.f, q = 0.f;
    uint4 a = ld_l2(row), b = ld_l2(row + 32), d = ld_l2(row + 64), e = ld_l2(row + 96);
    z_stats(a, s, q); a = ld_l2(row + 128);
    z_stats(b, s, q); b = ld_l2(row + 160);
    Z_NAP();
    z_stats(d, s, q); d = ld_l2(row + 192);
    z_stats(e, s, q);
    Z_NAP();
    z_stats(a, s, q); z_stats(b, s, q);
    Z_NAP();
    z_stats(d, s, q);
#pragma unroll
    for (int o = 16; o > 0; o >>= 1) {
        s += __shfl_xor_sync(0xffffffffu, s, o);
        q += __shfl_xor_sync(0xffffffffu, q, o);
    }
    Z_NAP();
    const float mean = s * (1.0f / FH_);
    const float r = bf_round(rsqrtf(fmaxf(q * (1.0f / FH_) - mean * mean, 0.f) + 1e-5f));
    const uint32_t r2 = pack_bf16(r, r), m2 = pack_bf16(-mean * r, -mean * r);
    row[96] = z_apply(e, r2, m2); e = ld_l2(row);
    row[128] = z_apply(a, r2, m2); a = ld_l2(row + 32);
    row[160] = z_apply(b, r2, m2); b = ld_l2(row + 64);
    row[192] = z_apply(d, r2, m2);
    row[0] = z_apply(e, r2, m2); row[32] = z_apply(a, r2, m2); row[64] = z_apply(b, r2, m2);
}

struct Cons {
    uint64_t desc0;
    uint32_t sbase;
    uint32_t rel;
    uint32_t seq;
    uint32_t par;
    uint32_t st;
    uint32_t stg_par;
    uint32_t wg, warp;
};

template <int TAG = 0>
__device__ __forceinline__ void c_wait_full(Cons& c, uint32_t idx) {
    mbar_wait<TAG>(c.sbase + BAR_OFF + 8 * (B_FULL + idx), c.par >> idx);
    c.par ^= 1u << idx;
}
__device__ __forceinline__ void c_release(const Cons& c, uint32_t idx, bool on = true) {
    mbar_arrive_cluster_if(c.rel + 8 * idx, on ? c.rel : 0u);
}

__device__ __forceinline__ uint32_t stage_base(const Cons& c) {
    const uint32_t lane = lane_id();
    const uint32_t row = c.warp * 16 + (lane & 7) + ((lane >> 3) & 1) * 8;
    return c.sbase + STG_OFF + c.wg * SLOT + row * 128 + (((lane >> 4) ^ (lane & 7)) << 4);
}
__device__ __forceinline__ uint32_t stage_begin(Cons& c) {
    mbar_wait(c.sbase + BAR_OFF + 8 * (B_STG_EMPTY + c.wg), c.stg_par);
    return stage_base(c);
}
__device__ __forceinline__ void stage_put(uint32_t base, int kk, uint32_t r0, uint32_t r1, uint32_t r2, uint32_t r3) {
    stsm4((base ^ ((kk & 3) << 5)) + (kk >> 2) * 8192, r0, r1, r2, r3);
}
__device__ __forceinline__ void stage_get(uint32_t base, int kk, uint32_t& r0, uint32_t& r1, uint32_t& r2, uint32_t& r3) {
    ldsm4((base ^ ((kk & 3) << 5)) + (kk >> 2) * 8192, r0, r1, r2, r3);
}
__device__ __forceinline__ void stage_end(Cons& c) {
    c.stg_par ^= 1;
    fence_proxy_async_smem();
    __syncwarp();
    mbar_arrive_lane0(c.sbase + BAR_OFF + 8 * (B_STG_FULL + c.wg));
}
__device__ __forceinline__ void stage_out(Cons& c, const uint32_t (&pk)[32]) {
    const uint32_t base = stage_begin(c);
#pragma unroll
    for (int kk = 0; kk < 8; kk++) stage_put(base, kk, pk[4 * kk], pk[4 * kk + 1], pk[4 * kk + 2], pk[4 * kk + 3]);
    stage_end(c);
}

__device__ __forceinline__ void stash_st(uint32_t stash, const uint32_t (&v)[32]) {
#pragma unroll
    for (int i = 0; i < 8; i++)
        asm volatile("st.shared.v4.b32 [%0], {%1,%2,%3,%4};" :: "r"(stash + (i >> 2) * 8192 + (i & 3) * 512),
                     "r"(v[4 * i]), "r"(v[4 * i + 1]), "r"(v[4 * i + 2]), "r"(v[4 * i + 3]) : "memory");
}
__device__ __forceinline__ void stash_ld(uint32_t stash, uint32_t (&v)[32]) {
#pragma unroll
    for (int i = 0; i < 8; i++)
        asm volatile("ld.shared.v4.b32 {%0,%1,%2,%3}, [%4];"
                     : "=r"(v[4 * i]), "=r"(v[4 * i + 1]), "=r"(v[4 * i + 2]), "=r"(v[4 * i + 3])
                     : "r"(stash + (i >> 2) * 8192 + (i & 3) * 512) : "memory");
}
enum : uint32_t { JOB_NONE = 0, JOB_GELU = 1, JOB_SILU = 2, JOB_ACT = 3, JOB_PUB = 4 };
template <int N> __device__ __forceinline__ void act_chunk(uint32_t addr, float c0, float c1) {
    uint32_t v[4 * N];
#pragma unroll
    for (int n = 0; n < N; n++)
        asm volatile("ld.shared.v4.b32 {%0,%1,%2,%3}, [%4];" : "=r"(v[4 * n]), "=r"(v[4 * n + 1]), "=r"(v[4 * n + 2]), "=r"(v[4 * n + 3])
                     : "r"(addr + n * 512) : "memory");
    float x[8 * N], u[8 * N];
#pragma unroll
    for (int i = 0; i < 8 * N; i++) {
        x[i] = (i & 1) ? bf_hi(v[i >> 1]) : bf_lo(v[i >> 1]);
        u[i] = tanh_fast(x[i] * fmaf(x[i] * x[i], c1, c0));
        x[i] *= 0.5f;
    }
    pin(x); pin(u);
    SCHED_FENCE();
#pragma unroll
    for (int i = 0; i < 4 * N; i++) v[i] = pack_bf16(fmaf(x[2 * i], u[2 * i], x[2 * i]), fmaf(x[2 * i + 1], u[2 * i + 1], x[2 * i + 1]));
#pragma unroll
    for (int n = 0; n < N; n++)
        asm volatile("st.shared.v4.b32 [%0], {%1,%2,%3,%4};" :: "r"(addr + n * 512), "r"(v[4 * n]), "r"(v[4 * n + 1]), "r"(v[4 * n + 2]),
                     "r"(v[4 * n + 3]) : "memory");
}
template <bool FIRST>
__device__ __forceinline__ void gemm_step(Cons& c, float (&acc)[128], uint32_t g) {
    c_wait_full(c, g);
    const uint64_t d = c.desc0 + (uint64_t)g * (3 * SLOT >> 4);
    const uint64_t da = d + c.wg * (8192 >> 4), db = d + ((SLOT >> 4) + DESC_MN);
    WG_FENCE();
    if (FIRST) wgmma_n256_init(acc, da, db);
    else wgmma_n256(acc, da, db);
    wgmma_n256(acc, da + 2, db + 128);
    wgmma_n256(acc, da + 4, db + 256);
    wgmma_n256(acc, da + 6, db + 384);
    WG_COMMIT();
}
__device__ __forceinline__ void pp_sync(uint32_t wg) { asm volatile("bar.sync %0, 256;" :: "r"(1 + wg) : "memory"); }
__device__ __forceinline__ void pp_arrive(uint32_t wg) { asm volatile("bar.arrive %0, 256;" :: "r"(2 - wg) : "memory"); }
__device__ __forceinline__ void gemm_main(Cons& c, float (&acc)[128], uint32_t nk, uint32_t job, uint32_t (&pk)[32],
                                          uint32_t stash, bool ordered, uint32_t solo) {
    uint32_t g = c.st;
    const bool pub = job & JOB_PUB;
    const bool si = job & JOB_SILU;
    const uint32_t mid = !job ? 999u : job == JOB_PUB ? 2u : pub ? 6u : si ? 5u : 9u;
    const uint32_t fast = pub ? (si ? 9u : 6u) : si ? 5u : 0u;
    const float c0 = si ? 0.5f : 0.7978845608028654f, c1 = si ? 0.f : 0.044715f * 0.7978845608028654f;
    uint32_t ch = (job & JOB_ACT) ? 0u : 8u;
    const uint32_t job_end = !job ? 0u : job == JOB_PUB ? 3u : 18u;
    gemm_step<true>(c, acc, g);
    if (ordered) nk--;
#pragma unroll 1
    for (uint32_t ks = 1; ks < nk; ks++) {
        const uint32_t prev = g;
        g = (g + 1) & 3;
        gemm_step<false>(c, acc, g);
        WG_WAIT(1);
        mbar_arrive_cluster_n_if(c.rel + 8 * prev, c.rel, ks > solo ? 2u : 1u);
        if (ks >= job_end) continue;
        if (ch < 8) {
            const uint32_t addr = stash + (ch >> 2) * 8192 + (ch & 3) * 512;
            if (ks < fast) { act_chunk<2>(addr, c0, c1); ch++; }
            else act_chunk<1>(addr, c0, c1);
            ch++;
            if (ch == 8 && pub) stage_end(c);
        } else if (ks == mid) {
            if (pub) {
                const uint32_t base = stage_begin(c);
#pragma unroll
                for (int kk = 0; kk < 8; kk++) stage_put(base, kk, pk[4 * kk], pk[4 * kk + 1], pk[4 * kk + 2], pk[4 * kk + 3]);
                if (!(job & JOB_ACT)) stage_end(c);
            } else {
                const uint32_t base = stage_base(c);
                __syncwarp();
                uint32_t r[32];
#pragma unroll
                for (int kk = 0; kk < 8; kk++) stage_get(base, kk, r[4 * kk], r[4 * kk + 1], r[4 * kk + 2], r[4 * kk + 3]);
                __syncwarp();
#pragma unroll
                for (int kk = 0; kk < 8; kk++) stage_put(base, kk, pk[4 * kk], pk[4 * kk + 1], pk[4 * kk + 2], pk[4 * kk + 3]);
#pragma unroll
                for (int i = 0; i < 32; i++) pk[i] = r[i];
            }
            __syncwarp();
            if (job & JOB_ACT) ch = 0;
        }
    }
    if (ordered) {
        const uint32_t prev = g;
        g = (g + 1) & 3;
        pp_sync(c.wg);
        gemm_step<false>(c, acc, g);
        pp_arrive(c.wg);
        WG_WAIT(1);
        c_release(c, prev);
    }
    WG_WAIT(0);
    pin(acc);
    mbar_arrive_cluster_n_if(c.rel + 8 * g, c.rel, nk > solo ? 2u : 1u);
    c.st = (g + 1) & 3;
}
template <int A>
__device__ __forceinline__ void sp_combine(uint32_t& z0, uint32_t& z1, uint32_t& z2, uint32_t& z3, const float (&acc)[128],
                                           uint32_t b0, uint32_t b1) {
    z0 = bf2_mul(z0, bf2_add(pack_bf16(acc[A], acc[A + 1]), b0));
    z1 = bf2_mul(z1, bf2_add(pack_bf16(acc[A + 2], acc[A + 3]), b1));
    z2 = bf2_mul(z2, bf2_add(pack_bf16(acc[A + 4], acc[A + 5]), b0));
    z3 = bf2_mul(z3, bf2_add(pack_bf16(acc[A + 6], acc[A + 7]), b1));
}
template <int H>
__device__ __forceinline__ void sp_half(uint32_t (&z)[32], const float (&acc)[128], uint32_t b0, uint32_t b1) {
    sp_combine<64 * H>(z[0], z[1], z[2], z[3], acc, b0, b1); sp_combine<64 * H + 8>(z[4], z[5], z[6], z[7], acc, b0, b1);
    sp_combine<64 * H + 16>(z[8], z[9], z[10], z[11], acc, b0, b1); sp_combine<64 * H + 24>(z[12], z[13], z[14], z[15], acc, b0, b1);
    sp_combine<64 * H + 32>(z[16], z[17], z[18], z[19], acc, b0, b1); sp_combine<64 * H + 40>(z[20], z[21], z[22], z[23], acc, b0, b1);
    sp_combine<64 * H + 48>(z[24], z[25], z[26], z[27], acc, b0, b1); sp_combine<64 * H + 56>(z[28], z[29], z[30], z[31], acc, b0, b1);
}
__device__ __forceinline__ void f_finish(Cons& c, uint32_t base, const uint32_t (&gu)[32], const float (&acc)[128], bool help,
                                         const CUtensorMap* mo, int row, int chunk) {
    uint32_t gl[32], u[64];
    const uint32_t sa = c.st * (3 * SLOT), sb = ((c.st + 1) & 3) * (3 * SLOT);
    const uint32_t rel = base - (STG_OFF + c.wg * SLOT);
    c_wait_full<1>(c, c.st);
#pragma unroll
    for (int kk = 0; kk < 8; kk++) stage_get(base, kk, gl[4 * kk], gl[4 * kk + 1], gl[4 * kk + 2], gl[4 * kk + 3]);
#pragma unroll
    for (int h = 0; h < 2; h++)
#pragma unroll
        for (int kk = 0; kk < 8; kk++) {
            uint32_t xr[4];
            stage_get(rel + sa + h * SLOT, kk, xr[0], xr[1], xr[2], xr[3]);
#pragma unroll
            for (int i = 0; i < 4; i++)
                u[32 * h + 4 * kk + i] = bf2_fma(pack_bf16(acc[64 * h + 8 * kk + 2 * i], acc[64 * h + 8 * kk + 2 * i + 1]),
                                                 h ? gu[4 * kk + i] : gl[4 * kk + i], xr[i]);
        }
    pin(u);
    __syncwarp();
    c_wait_full<2>(c, (c.st + 1) & 3);
    if (help) {
#pragma unroll
        for (int i = 0; i < 16; i++) {
            uint32_t hv[4];
            stage_get(rel + sb + (1 + (i >> 3)) * SLOT, i & 7, hv[0], hv[1], hv[2], hv[3]);
#pragma unroll
            for (int k = 0; k < 4; k++) u[4 * i + k] = bf2_fma(hv[k], i >= 8 ? gu[4 * (i & 7) + k] : gl[4 * (i & 7) + k], u[4 * i + k]);
        }
    }
#pragma unroll
    for (int h = 0; h < 2; h++) {
        const uint32_t pa = c.sbase + (h ? sb : sa + 2 * SLOT) + (c.warp * 32 + lane_id()) * 16;
#pragma unroll
        for (int kk = 0; kk < 8; kk++) {
            uint32_t pv[4];
            asm volatile("ld.shared.v4.b32 {%0,%1,%2,%3}, [%4];" : "=r"(pv[0]), "=r"(pv[1]), "=r"(pv[2]), "=r"(pv[3])
                         : "r"(pa + kk * 2048) : "memory");
#pragma unroll
            for (int i = 0; i < 4; i++)
                u[32 * h + 4 * kk + i] = bf2_fma(pv[i], h ? gu[4 * kk + i] : gl[4 * kk + i], u[32 * h + 4 * kk + i]);
        }
#pragma unroll
        for (int kk = 0; kk < 8; kk++)
            stage_put(rel + sa + h * SLOT, kk, u[32 * h + 4 * kk], u[32 * h + 4 * kk + 1], u[32 * h + 4 * kk + 2], u[32 * h + 4 * kk + 3]);
        fence_proxy_async_smem();
        asm volatile("bar.sync %0, 128;" :: "r"(3 + c.wg) : "memory");
        if (c.warp == 0 && elect_one()) tma_3d_store(mo, c.sbase + sa + h * SLOT, row, chunk + 2 * h);
        __syncwarp();
    }
    if (c.warp == 0) {
        asm volatile("cp.async.bulk.commit_group;" ::: "memory");
        asm volatile("cp.async.bulk.wait_group.read 0;" ::: "memory");
    }
}

constexpr float SM_C = 0.08838834764831845f * 1.4426950408889634f;

__device__ __forceinline__ void issue_qk(const Cons& c, float (&s)[64], const uint32_t (&q)[32], uint32_t stage) {
    const uint64_t d = c.desc0 + stage * (2 * SLOT >> 4);
    wgmma_n128_rs_init<0>(s, q[0], q[1], q[2], q[3], d);
#pragma unroll
    for (int kk = 1; kk < 8; kk++)
        wgmma_n128_rs<0>(s, q[4 * kk], q[4 * kk + 1], q[4 * kk + 2], q[4 * kk + 3], d + ((kk >> 2) * (SLOT >> 4) + (kk & 3) * 2), 1);
}
__device__ __forceinline__ void issue_pv(const Cons& c, float (&o)[64], const uint32_t (&p)[32], uint32_t stage, uint32_t acc) {
    const uint64_t d = c.desc0 + (stage * (2 * SLOT >> 4) + DESC_MN);
#pragma unroll
    for (int kk = 0; kk < 8; kk++)
        wgmma_n128_rs<1>(o, p[4 * kk], p[4 * kk + 1], p[4 * kk + 2], p[4 * kk + 3], d + ((kk >> 2) * (SLOT >> 4) + (kk & 3) * 128),
                         kk ? 1u : acc);
}
__device__ __forceinline__ void row_max(const float (&s)[64], float& m0, float& m1) {
    float a0 = fmaxf(s[0], s[1]), a1 = fmaxf(s[2], s[3]), b0 = fmaxf(s[4], s[5]), b1 = fmaxf(s[6], s[7]);
#pragma unroll
    for (int i = 2; i < 16; i += 2) {
        a0 = fmaxf(a0, fmaxf(s[4 * i], s[4 * i + 1]));
        a1 = fmaxf(a1, fmaxf(s[4 * i + 2], s[4 * i + 3]));
        b0 = fmaxf(b0, fmaxf(s[4 * i + 4], s[4 * i + 5]));
        b1 = fmaxf(b1, fmaxf(s[4 * i + 6], s[4 * i + 7]));
    }
    m0 = fmaxf(a0, b0); m1 = fmaxf(a1, b1);
    m0 = fmaxf(m0, __shfl_xor_sync(0xffffffffu, m0, 1));
    m1 = fmaxf(m1, __shfl_xor_sync(0xffffffffu, m1, 1));
    m0 = fmaxf(m0, __shfl_xor_sync(0xffffffffu, m0, 2));
    m1 = fmaxf(m1, __shfl_xor_sync(0xffffffffu, m1, 2));
}
__device__ __forceinline__ void sub_rows(float (&s)[64], float m0, float m1) {
#pragma unroll
    for (int i = 0; i < 16; i++) { s[4 * i] -= m0; s[4 * i + 1] -= m0; s[4 * i + 2] -= m1; s[4 * i + 3] -= m1; }
}
template <int R> __device__ __forceinline__ void exp_q(float (&s)[64]) {
#pragma unroll
    for (int i = 0; i < 8; i++) {
        const int b = 32 * (R >> 1) + 4 * i + 2 * (R & 1);
        s[b] = ex2(s[b]); s[b + 1] = ex2(s[b + 1]);
    }
}
template <int R, int HF> __device__ __forceinline__ void exp_h(float (&s)[64]) {
#pragma unroll
    for (int i = 4 * HF; i < 4 * HF + 4; i++) {
        const int b = 32 * (R >> 1) + 4 * i + 2 * (R & 1);
        s[b] = ex2(s[b]); s[b + 1] = ex2(s[b + 1]);
    }
}
template <int R> __device__ __forceinline__ uint32_t sum_q(const uint32_t (&p)[32]) {
    const int b = 16 * (R >> 1) + (R & 1);
    return bf2_add(bf2_add(bf2_add(p[b], p[b + 2]), bf2_add(p[b + 4], p[b + 6])),
                   bf2_add(bf2_add(p[b + 8], p[b + 10]), bf2_add(p[b + 12], p[b + 14])));
}
__device__ __forceinline__ float sum_fin(uint32_t a, uint32_t b) {
    a = bf2_add(a, b);
    return bf_lo(a) + bf_hi(a);
}
template <int R> __device__ __forceinline__ void pack_q(const float (&s)[64], uint32_t (&p)[32]) {
#pragma unroll
    for (int i = 0; i < 8; i++) {
        const int b = 32 * (R >> 1) + 4 * i + 2 * (R & 1);
        asm volatile("cvt.rn.bf16x2.f32 %0, %1, %2;" : "=r"(p[b >> 1]) : "f"(s[b + 1]), "f"(s[b]));
    }
}
__device__ __forceinline__ void attn_recip(float& l0, float& l1) {
    l0 += __shfl_xor_sync(0xffffffffu, l0, 1); l1 += __shfl_xor_sync(0xffffffffu, l1, 1);
    l0 += __shfl_xor_sync(0xffffffffu, l0, 2); l1 += __shfl_xor_sync(0xffffffffu, l1, 2);
    l0 = __fdividef(1.0f, l0); l1 = __fdividef(1.0f, l1);
}
template <int K0, int K1>
__device__ __forceinline__ void attn_put_o(uint32_t base, const float (&o)[64], float r0, float r1) {
#pragma unroll
    for (int kk = K0; kk < K1; kk++) {
        stage_put(base, kk, pack_bf16(o[8 * kk] * r0, o[8 * kk + 1] * r0), pack_bf16(o[8 * kk + 2] * r1, o[8 * kk + 3] * r1),
                  pack_bf16(o[8 * kk + 4] * r0, o[8 * kk + 5] * r0), pack_bf16(o[8 * kk + 6] * r1, o[8 * kk + 7] * r1));
        if (kk & 1) SCHED_FENCE();
    }
}

__device__ __forceinline__ uint32_t nxt6(uint32_t a) { return a == 5 ? 0 : a + 1; }

constexpr float SM_FLOOR = 1.0f / 16777216.0f;
constexpr float SM_LIMIT = 1099511627776.0f;
__device__ __forceinline__ bool sm_flagged(uint32_t flag, uint32_t seq) {
    uint32_t f;
    asm volatile("ld.volatile.shared.u32 %0, [%1];" : "=r"(f) : "r"(flag) : "memory");
    return __any_sync(0xffffffffu, f == seq);
}
struct SmState { float m0, m1, l0, l1, t0, t1; uint32_t sub; };
__device__ __forceinline__ void softmax_fix(const Cons& c, SmState& st, float (&s)[64], float (&o)[64], uint32_t (&p)[32],
                                            const uint32_t (&q)[32], uint32_t kstage, bool first) {
    asm volatile("bar.sync %0, 128;" :: "r"(3 + c.wg) : "memory");
    WG_FENCE();
    issue_qk(c, s, q, kstage);
    WG_COMMIT();
    WG_WAIT(0);
    pin(s);
    float n0, n1;
    row_max(s, n0, n1);
    if (first) { st.m0 = n0; st.m1 = n1; }
    n0 = fmaxf(n0, st.m0); n1 = fmaxf(n1, st.m1);
    const float al0 = ex2(st.m0 - n0), al1 = ex2(st.m1 - n1);
    st.m0 = n0; st.m1 = n1;
    st.sub = 1;
    st.l0 *= al0; st.l1 *= al1;
#pragma unroll
    for (int i = 0; i < 16; i++) {
        o[4 * i] *= al0; o[4 * i + 1] *= al0; o[4 * i + 2] *= al1; o[4 * i + 3] *= al1;
    }
    sub_rows(s, n0, n1);
    pin(s); SCHED_FENCE();
    exp_q<0>(s); exp_q<1>(s); exp_q<2>(s); exp_q<3>(s);
    pin(s); SCHED_FENCE();
    pack_q<0>(s, p); pack_q<1>(s, p); pack_q<2>(s, p); pack_q<3>(s, p);
    st.t0 = sum_fin(sum_q<0>(p), sum_q<2>(p)); st.t1 = sum_fin(sum_q<1>(p), sum_q<3>(p));
    pin(s); pin(o); pin(p);
}
__device__ __forceinline__ void attention2(Cons& c, float (&acc)[128], uint32_t stash) {
    float o[64], s[64];
    uint32_t p[32], q[32];
#pragma unroll
    for (int i = 0; i < 32; i++) q[i] = pack_bf16(acc[2 * i] * SM_C, acc[2 * i + 1] * SM_C);
    SmState st = {0.f, 0.f, 0.f, 0.f, 0.f, 0.f, 0u};
    const uint32_t flag = c.sbase + BAR_OFF + 8 * (B_FLAG + c.wg);
    uint32_t ka = g2a(c.st);
    uint32_t va = 0;
    uint32_t a = nxt6(ka);
    c_wait_full(c, 4 + ka);
    pp_sync(c.wg);
    pin(q);
    WG_FENCE();
    issue_qk(c, s, q, ka);
    WG_COMMIT();
    pp_arrive(c.wg);
    SCHED_FENCE();
#pragma unroll
    for (int i = 64; i < 128; i++) asm volatile("" : "+f"(acc[i]) :: "memory");
#pragma unroll
    for (int i = 0; i < 32; i++) p[i] = pack_bf16(acc[64 + 2 * i] * SM_C, acc[64 + 2 * i + 1] * SM_C);
    stage_begin(c);
    stash_st(stash, p);
#pragma unroll
    for (int i = 0; i < 64; i++) o[i] = 0.f;
    pin(o); pin(p);
    SCHED_FENCE();
    WG_WAIT(0);
    uint32_t t = 0, kprev;
#pragma unroll 1
    while (true) {
        pin(s);
        if (c.seq == 0xffffffffu) { WG_WAIT(0); stash_st(stash, p); }
        if (st.sub) sub_rows(s, st.m0, st.m1);
        bool done_pv;
#pragma unroll 1
        do {
            pin(s);
            exp_q<0>(s); exp_q<1>(s); exp_h<2, 0>(s);
            pin(s); SCHED_FENCE();
            WG_WAIT(0);
            pin(o); pin(s);
            c_release(c, 4 + va, t != 0);
            exp_h<2, 1>(s); pack_q<0>(s, p); pack_q<1>(s, p);
            pin(s); SCHED_FENCE();
            exp_h<3, 0>(s);
            uint32_t h0 = sum_q<0>(p), h1 = sum_q<1>(p);
            pin(s); asm volatile("" : "+r"(h0), "+r"(h1)); SCHED_FENCE();
            exp_h<3, 1>(s); pack_q<2>(s, p);
            st.t0 = sum_fin(h0, sum_q<2>(p));
            pin(s);
            asm volatile("" : "+f"(st.t0), "+r"(h1));
            c_wait_full(c, 4 + a);
            pack_q<3>(s, p);
            st.t1 = sum_fin(h1, sum_q<3>(p));
            const float floor_ = (t & 15) ? 0.f : SM_FLOOR;
            if (!(st.t0 <= SM_LIMIT && st.t1 <= SM_LIMIT && st.t0 >= floor_ && st.t1 >= floor_))
                asm volatile("st.volatile.shared.u32 [%0], %1;" :: "r"(flag), "r"(c.seq) : "memory");
            t++;
            if (t == 17) attn_put_o<0, 6>(stash, o, st.l0, st.l1);
            pp_sync(c.wg);
            pin(o); pin(p); pin(q); pin(s);
            done_pv = false;
            kprev = ka; ka = a; va = nxt6(a); a = nxt6(va);
            if ((t & 15) == 0) break;
            WG_FENCE();
            issue_qk(c, s, q, ka);
            WG_COMMIT();
            SCHED_FENCE();
            if (sm_flagged(flag, c.seq)) { WG_WAIT(0); pin(s); break; }
            c_release(c, 4 + kprev);
            if (t == 17) {
                attn_put_o<6, 8>(stash, o, st.l0, st.l1);
                st.l0 = 0.f; st.l1 = 0.f;
                pin(o);
            }
            if (t == 18) stage_end(c);
            st.l0 += st.t0; st.l1 += st.t1;
            c.seq++;
            c_wait_full(c, 4 + va);
            WG_FENCE();
            issue_pv(c, o, p, va, t != 17);
            WG_COMMIT();
            pp_arrive(c.wg);
            WG_WAIT(1);
            done_pv = true;
        } while (!st.sub);
        if (done_pv) continue;
        if (sm_flagged(flag, c.seq)) softmax_fix(c, st, s, o, p, q, kprev, (t & 15) == 1);
        c_release(c, 4 + kprev);
        c.seq++;
        if (t == 17) { attn_put_o<6, 8>(stash, o, st.l0, st.l1); st.l0 = 0.f; st.l1 = 0.f; pin(o); }
        if (t == 18) stage_end(c);
        st.l0 += st.t0; st.l1 += st.t1;
        if (t == 32) break;
        if (t == 16) { stash_ld(stash, q); st.m0 = 0.f; st.m1 = 0.f; st.sub = 0; }
        pin(q);
        WG_FENCE();
        issue_qk(c, s, q, ka);
        WG_COMMIT();
        if (t == 16) {
            SCHED_FENCE();
            attn_recip(st.l0, st.l1);
            const uint32_t l16 = stash & 0x1f0;
            stash = (stash - l16) + (l16 & 0xf0) * 8 + (((l16 >> 4) ^ l16) & 0x70);
        }
        c_wait_full(c, 4 + va);
        WG_FENCE();
        issue_pv(c, o, p, va, t != 17);
        WG_COMMIT();
        pp_arrive(c.wg);
        WG_WAIT(1);
    }
    WG_FENCE();
    issue_pv(c, o, p, ka, 1);
    WG_COMMIT();
    pp_arrive(c.wg);
    attn_recip(st.l0, st.l1);
    stage_begin(c);
    WG_WAIT(0);
    pin(o);
    c_release(c, 4 + ka);
    attn_put_o<0, 8>(stash, o, st.l0, st.l1);
    stage_end(c);
    c.st = a2g(va);
}

struct Prod {
    uint32_t sbase, par, st, rank, lane;
};
__device__ __forceinline__ void p_wait_empty(const Prod& p, uint32_t idx) {
    mbar_wait(p.sbase + BAR_OFF + 8 * (B_EMPTY + idx), (p.par >> idx) & 1);
}
__device__ __forceinline__ void p_acquire_g(Prod& p, uint32_t g) {
    uint32_t a0 = (3 * g) >> 1;
    p_wait_empty(p, 4 + a0);
    p_wait_empty(p, 5 + a0);
    p_wait_empty(p, g);
    p.par ^= 1u << g;
}
__device__ __forceinline__ void p_acquire_a(Prod& p, uint32_t a) {
    p_wait_empty(p, (2 * a) / 3);
    p_wait_empty(p, (2 * a + 1) / 3);
    p_wait_empty(p, 4 + a);
    p.par ^= 1u << (4 + a);
}

__device__ __forceinline__ const CUtensorMap* uniform_ptr(const CUtensorMap* p) {
    return reinterpret_cast<const CUtensorMap*>(__shfl_sync(0xffffffffu, reinterpret_cast<unsigned long long>(p), 0));
}
enum { DEP_A_ONE = 0, DEP_A_XN, DEP_A_HEAD, DEP_B_RB };

}

__global__ void __cluster_dims__(2, 1, 1) __launch_bounds__(384, 1)
fused_kernel(const __grid_constant__ Params prm) {
    extern __shared__ __align__(1024) uint8_t smem_raw[];
    const uint32_t sbase = smem_u32(smem_raw);
    const uint32_t lane = threadIdx.x & 31;
    const uint32_t warp_id = __shfl_sync(0xffffffffu, threadIdx.x >> 5, 0);
    uint32_t rank;
    asm volatile("mov.u32 %0, %%cluster_ctarank;" : "=r"(rank));
    const uint32_t pair = blockIdx.x >> 1;

    if (warp_id < 4) {
        uint32_t exits = 0;
        if (warp_id == 3) exits = ld_relaxed(&g_cnt[C_EXIT]);
        if (threadIdx.x == 0) {
            if (sbase & 1023) die();
            for (int i = 0; i < 10; i++) {
                asm volatile("mbarrier.init.shared::cta.b64 [%0], 1;" :: "r"(sbase + BAR_OFF + 8 * (B_FULL + i)));
                asm volatile("mbarrier.init.shared::cta.b64 [%0], 16;" :: "r"(sbase + BAR_OFF + 8 * (B_EMPTY + i)));
            }
            for (int i = 0; i < 2; i++) {
                asm volatile("mbarrier.init.shared::cta.b64 [%0], 4;" :: "r"(sbase + BAR_OFF + 8 * (B_STG_FULL + i)));
                asm volatile("mbarrier.init.shared::cta.b64 [%0], 1;" :: "r"(sbase + BAR_OFF + 8 * (B_STG_EMPTY + i)));
            }
            asm volatile("mbarrier.init.shared::cta.b64 [%0], 1;" :: "r"(sbase + BAR_OFF + 8 * B_EPOCH_BAR));
            asm volatile("mbarrier.init.shared::cta.b64 [%0], 2;" :: "r"(sbase + BAR_OFF + 8 * B_GATE));
            asm volatile("fence.mbarrier_init.release.cluster;" ::: "memory");
        }
        __syncwarp();
        asm volatile("barrier.cluster.arrive.relaxed.aligned;" ::: "memory");
        asm volatile("setmaxnreg.dec.sync.aligned.u32 40;");
        asm volatile("barrier.cluster.wait.acquire.aligned;" ::: "memory");
        if (warp_id == 0) {
            Prod pr{sbase, 0x3ffu, 0, rank, lane};
            uint32_t z2n_mask = 0, xn_mask = 0, tail = 0;
            {
                const uint32_t it = prm.sched[pair][0];
                if (elect_one()) {
                    for (uint32_t g = 0; g < NRAW; g++) {
                        const uint32_t bar = sbase + BAR_OFF + 8 * (B_FULL + g);
                        mbar_expect_tx(bar, 3 * SLOT);
                        tma_3d_mc(sbase + g * (3 * SLOT) + SLOT + rank * SLOT, &prm.maps[it_type(it) == T_ATT ? M_WQ : M_WIN], g * 64,
                                  (it_type(it) == T_ATT ? 0 : 28) + 4 * it_j(it) + 2 * rank, bar);
                    }
                }
                __syncwarp();
                if (lane < M_COUNT) asm volatile("prefetch.tensormap [%0];" :: "l"(&prm.maps[lane]) : "memory");
                __syncwarp();
                if (elect_one()) {
                    for (uint32_t g = 0; g < NRAW; g++)
                        tma_2d(sbase + g * (3 * SLOT), &prm.maps[M_XRAW], g * 64, (it_p(it) * 2 + rank) * 128, sbase + BAR_OFF + 8 * (B_FULL + g));
                }
                __syncwarp();
            }
            const uint32_t epoch = get_epoch(sbase);
            for (int ii = 0; ii < MAX_ITEMS; ii++) {
                const uint32_t it = prm.sched[pair][ii];
                const uint32_t ty = it_type(it);
                if (ty == T_END) break;
                const uint32_t rb = it_p(it) * 2 + rank, j = it_j(it);
                const int row0 = rb * 128;
                const int nseg = (ty == T_SP || ty == T_FX) ? 2 : 1;
                uint32_t o_mask = 0;
                for (int seg = 0; seg < nseg; seg++) {
                    uint32_t iA, iB;
                    uint32_t k0 = 0, k1, chunk, dep, cidx = 0, target = 0;
                    if (ty == T_Z2)       { iA = M_XN; iB = M_WIN; k1 = 16; chunk = 28 + 4 * j; dep = DEP_A_XN; cidx = C_XN + rb * CS; target = 8 * epoch; }
                    else if (ty == T_ATT) { iA = M_XN; iB = M_WQ;  k1 = 16; chunk = 4 * j; dep = DEP_A_XN; cidx = C_XN + rb * CS; target = 8 * epoch; }
                    else if (ty == T_SP && seg == 0) { iA = M_XN; iB = M_WIN; k1 = 16; chunk = 4 * j; dep = DEP_A_XN; cidx = C_XN + rb * CS; target = 8 * epoch; }
                    else if (ty == T_SP)  { iA = M_WSP; iB = M_Z2; k1 = 32; chunk = 4 * j; dep = DEP_B_RB; }
                    else if (ty == T_FX && seg == 0) { iA = M_H_LD; iB = M_WOUT; k1 = 28; chunk = 4 * j; dep = DEP_A_ONE; cidx = C_H + rb * CS; target = 14 * epoch; }
                    else {
                        iA = M_O_LD; iB = M_WO; chunk = 4 * j; dep = DEP_A_HEAD;
                        k0 = ty == T_FX ? it_k1(it) : ty == T_FY ? it_kh(it) : 0;
                        k1 = ty == T_FX ? 64 : ty == T_FY ? it_k0(it) : it_kh(it);
                    }
                    chunk += 2 * rank;
                    const CUtensorMap* mA = uniform_ptr(&prm.maps[iA]);
                    const CUtensorMap* mB = uniform_ptr(&prm.maps[iB]);
                    if (ii == 0 && seg == 0) {
                        asm volatile("bar.sync 5, 288;" ::: "memory");
                        if (elect_one()) {
                            if (blockIdx.x < 128) red_release(&g_cnt[C_XN + (blockIdx.x >> 3) * CS]);
                            for (uint32_t g = NRAW; g < 4; g++) {
                                mbar_expect_tx(sbase + BAR_OFF + 8 * (B_FULL + g), 3 * SLOT);
                                tma_3d_mc(sbase + g * (3 * SLOT) + SLOT + rank * SLOT, mB, g * 64, chunk, sbase + BAR_OFF + 8 * (B_FULL + g));
                            }
                        }
                        __syncwarp();
                        poll_one(&g_cnt[cidx], target);
                        if (elect_one()) {
                            for (uint32_t g = NRAW; g < 4; g++)
                                tma_2d(sbase + g * (3 * SLOT), mA, g * 64, row0, sbase + BAR_OFF + 8 * (B_FULL + g));
                        }
                        __syncwarp();
                        pr.par ^= 0xf;
                        k0 = 4;
                    } else if (dep == DEP_A_ONE) poll_one(&g_cnt[cidx], target);
                    else if (dep == DEP_A_XN) poll_mask(&g_cnt[C_XN], 16, CS, 8 * epoch, rb, xn_mask, lane);
                    for (uint32_t ks = k0; ks < k1; ks++) {
                        if (dep == DEP_B_RB) poll_mask(&g_cnt[C_Z2N], 16, CS, 128 * epoch, ks >> 1, z2n_mask, lane);
                        else if (dep == DEP_A_HEAD) poll_mask(&g_cnt[C_O + rb * 32], 32, 1, 2 * epoch, ks >> 1, o_mask, lane);
                        const uint32_t g = pr.st;
                        pr.st = (g + 1) & 3;
                        const uint32_t bar = sbase + BAR_OFF + 8 * (B_FULL + g);
                        const uint32_t sa = sbase + g * (3 * SLOT);
                        p_acquire_g(pr, g);
                        if (elect_one()) {
                            mbar_expect_tx(bar, 3 * SLOT);
                            tma_3d_mc(sa + SLOT + rank * SLOT, mB, ks * 64, chunk, bar);
                            tma_2d(sa, mA, ks * 64, row0, bar);
                        }
                        __syncwarp();
                    }
                }
                if (ty == T_ATT) {
                    uint32_t a = g2a(pr.st);
                    const int kv0 = j * 2 * S_;
                    const CUtensorMap *mK = uniform_ptr(&prm.maps[M_K]), *mV = uniform_ptr(&prm.maps[M_V]);
                    for (int t = 0; t < 33; t++) {
                        if (t < 32) {
                            p_acquire_a(pr, a);
                            const uint32_t bar = sbase + BAR_OFF + 8 * (B_FULL + 4 + a);
                            if (elect_one()) {
                                mbar_expect_tx(bar, 2 * SLOT);
                                tma_2d_mc(sbase + a * (2 * SLOT) + rank * SLOT, mK, rank * 64, kv0 + t * 128, bar);
                            }
                            a = nxt6(a);
                        }
                        if (t > 0) {
                            p_acquire_a(pr, a);
                            const uint32_t bar = sbase + BAR_OFF + 8 * (B_FULL + 4 + a);
                            if (elect_one()) {
                                mbar_expect_tx(bar, 2 * SLOT);
                                tma_3d_mc(sbase + a * (2 * SLOT) + rank * SLOT, mV, kv0 + (t - 1) * 128 + rank * 64, 0, bar);
                            }
                            a = nxt6(a);
                        }
                        __syncwarp();
                    }
                    pr.st = a2g(a);
                } else if (ty == T_FX || ty == T_FY) {
                    const uint32_t own = ty == T_FY;
                    const CUtensorMap *mA = uniform_ptr(&prm.maps[M_O_LD64]), *mB = uniform_ptr(&prm.maps[M_WO]);
                    for (uint32_t ks = it_k0(it); ks < it_k1(it); ks++) {
                        const uint32_t g = pr.st;
                        pr.st = (g + 1) & 3;
                        const uint32_t bar = sbase + BAR_OFF + 8 * (B_FULL + g);
                        const uint32_t sa = sbase + g * (3 * SLOT);
                        poll_mask(&g_cnt[C_O + rb * 32], 32, 1, 2 * epoch, ks >> 1, o_mask, lane);
                        p_acquire_g(pr, g);
                        if (elect_one()) {
                            mbar_expect_tx(bar, 2 * SLOT + 8192);
                            tma_3d_mc(sa + SLOT + rank * SLOT, mB, ks * 64, 4 * j + 2 * rank, bar);
                            tma_2d(sa + own * 8192, mA, ks * 64, row0 + own * 64, bar);
                        }
                        __syncwarp();
                    }
                    const uint32_t ga = pr.st, gb = (ga + 1) & 3;
                    const uint32_t bara = sbase + BAR_OFF + 8 * (B_FULL + ga), barb = sbase + BAR_OFF + 8 * (B_FULL + gb);
                    const uint32_t sa = sbase + ga * (3 * SLOT), sb = sbase + gb * (3 * SLOT);
                    pr.st = (ga + 2) & 3;
                    p_acquire_g(pr, ga);
                    if (elect_one()) {
                        asm volatile("prefetch.tensormap [%0];" :: "l"(&prm.maps[M_OUT]) : "memory");
                        mbar_expect_tx(bara, 2 * SLOT);
                        tma_3d(sa, &prm.maps[M_X], row0 + own * 64, 4 * j, bara);
                        tma_3d(sa + SLOT, &prm.maps[M_X], row0 + own * 64, 4 * j + 2, bara);
                    }
                    __syncwarp();
                    if (it_kh(it)) poll_one(&g_cnt[C_HELP + rb * CS], 2 * epoch);
                    p_acquire_g(pr, gb);
                    if (elect_one()) {
                        mbar_expect_tx(barb, it_kh(it) ? 4 * SLOT : 2 * SLOT);
                        if (it_kh(it)) {
                            tma_3d(sb + SLOT, &prm.maps[M_HELP], row0 + own * 64, 0, barb);
                            tma_3d(sb + 2 * SLOT, &prm.maps[M_HELP], row0 + own * 64, 2, barb);
                        }
                    }
                    __syncwarp();
                    poll_one(&g_cnt[C_PART + ((rb * 4 + j) * 2 + own) * CS], 4 * epoch);
                    if (elect_one()) {
                        const uint32_t* src = g_part + (size_t)((rb * 4 + j) * 2 + own) * 8192;
                        bulk_ld(sa + 2 * SLOT, src, SLOT, barb);
                        bulk_ld(sb, src + 4096, SLOT, barb);
                    }
                    __syncwarp();
                }
                tail = (ty == T_FX || ty == T_FY) ? 2 : 4;
            }
            for (uint32_t n = 0; n < tail; n++) p_wait_empty(pr, (pr.st + n) & 3);
        } else {
            const uint32_t w = warp_id - 1;
            const uint32_t next = sbase + BAR_OFF + 8 * B_NEXT;
            if (w == 2 && lane == 0) {
                asm volatile("st.volatile.shared.u32 [%0], %1;" :: "r"(next), "r"(blockIdx.x < 128 ? 0 : 16) : "memory");
                asm volatile("st.volatile.shared.u32 [%0], %1;" :: "r"(sbase + BAR_OFF + 8 * B_EPOCH), "r"(exits / (2 * NPAIR) + 1) : "memory");
                mbar_arrive(sbase + BAR_OFF + 8 * B_EPOCH_BAR);
            }
            __syncwarp();
            const uint32_t epoch = get_epoch(sbase);
            uint32_t full_par = 0;
            uint32_t nrb = 0;
            const uint32_t nap = it_type(prm.sched[pair][1]) == T_Z2 ? 0 : 400;
            auto try_norm = [&]() -> bool {
                uint32_t v;
                asm volatile("ld.volatile.shared.u32 %0, [%1];" : "=r"(v) : "r"(next) : "memory");
                nrb = __shfl_sync(0xffffffffu, v, 0);
                if (nrb >= 16) return true;
                uint32_t ok = (int32_t)(ld_relaxed(&g_cnt[C_Z2 + nrb * CS]) - 14 * epoch) >= 0;
                if (!__all_sync(0xffffffffu, ok)) return false;
                if (lane == 0) asm volatile("atom.shared.cas.b32 %0, [%1], %2, %3;" : "=r"(v) : "r"(next), "r"(nrb), "r"(nrb + 1) : "memory");
                if (__shfl_sync(0xffffffffu, v, 0) != nrb) return true;
                fence_acquire();
                fence_proxy_async_all();
                ln_z_row(reinterpret_cast<uint4*>(g_z2 + (size_t)(nrb * 128 + blockIdx.x) * FH_) + lane, nap);
                fence_proxy_async_all();
                __syncwarp();
                if (lane == 0) red_release(&g_cnt[C_Z2N + nrb * CS]);
                return true;
            };
            for (int ii = 0; ii < MAX_ITEMS && w < 2; ii++) {
                const uint32_t it = prm.sched[pair][ii];
                const uint32_t ty = it_type(it);
                if (ty == T_END) break;
                const uint32_t rb = it_p(it) * 2 + rank, j = it_j(it);
                if (ty == T_FY) {
                    poll_one(&g_cnt[C_GATE + (rb * 4 + j) * CS], epoch);
                    if (lane == 0) {
                        mbar_expect_tx(sbase + BAR_OFF + 8 * B_GATE, SLOT);
                        tma_3d(sbase + STG_OFF + w * SLOT, &prm.maps[M_GATE], rb * 128 + 64, 4 * j + 2 * (1 - w), sbase + BAR_OFF + 8 * B_GATE);
                    }
                    __syncwarp();
                    continue;
                }
                if (ty == T_FX && w == 0) continue;
                const CUtensorMap* m = &prm.maps[ty == T_Z2 ? M_Z2 : ty == T_ATT ? M_O_ST : ty == T_SP ? M_H_ST : ty == T_FX ? M_GATE : M_HELP];
                for (uint32_t e = 0; e < 2; e++) {
                    const uint32_t fb = sbase + BAR_OFF + 8 * (B_STG_FULL + w);
                    uint32_t t0 = (uint32_t)clock();
                    while (nrb < 16 && ty != T_Z2 && !__all_sync(0xffffffffu, mbar_test(fb, full_par))) {
                        if (!try_norm()) __nanosleep(1000);
                        if ((uint32_t)clock() - t0 > 2000000000u) die();
                    }
                    mbar_wait(fb, full_par);
                    full_par ^= 1;
                    if (lane == 0) {
                        tma_3d_store(m, sbase + STG_OFF + w * SLOT, rb * 128 + w * 64, 4 * j + 2 * (ty == T_ATT || ty == T_SP ? e : 1 - e));
                        asm volatile("cp.async.bulk.commit_group;" ::: "memory");
                        asm volatile("cp.async.bulk.wait_group.read 0;" ::: "memory");
                        mbar_arrive(sbase + BAR_OFF + 8 * (B_STG_EMPTY + w));
                        if (ty == T_ATT || e == 1) {
                            asm volatile("cp.async.bulk.wait_group 0;" ::: "memory");
                            fence_proxy_async_all();
                            if (ty == T_ATT) red_release(&g_cnt[C_O + rb * 32 + 2 * j + e]);
                            else if (ty == T_Z2) red_release(&g_cnt[C_Z2 + rb * CS]);
                            else if (ty == T_FX) red_release(&g_cnt[C_GATE + (rb * 4 + j) * CS]);
                            else red_release(&g_cnt[(ty == T_SP ? C_H : C_HELP) + rb * CS]);
                        }
                    }
                    __syncwarp();
                }
            }
            uint32_t t0 = (uint32_t)clock();
            while (nrb < 16) {
                if (!try_norm()) __nanosleep(1000);
                if ((uint32_t)clock() - t0 > 2000000000u) die();
            }
        }
    } else {
        const uint32_t r0 = (blockIdx.x & 127) * 16 + (warp_id - 4) * 2 + (lane >> 4);
        uint4 xv[8];
        if (blockIdx.x < 128) {
            const uint4* src = reinterpret_cast<const uint4*>(prm.x + (size_t)r0 * D_) + (lane & 15);
#pragma unroll
            for (int i = 0; i < 8; i++) xv[i] = __ldg(src + i * 16);
        }
        asm volatile("barrier.cluster.arrive.relaxed.aligned;" ::: "memory");
        asm volatile("setmaxnreg.inc.sync.aligned.u32 232;");
        Cons c;
        c.desc0 = ((uint64_t)(DESC_HI | prm.zero) << 32) | ((sbase & 0x3FFFF) >> 4) | (1u << 16);
        c.sbase = sbase; c.par = 0; c.st = 0; c.stg_par = 1; c.seq = 1;
        c.wg = (warp_id >> 2) - 1; c.warp = warp_id & 3;
        {
            uint32_t la = sbase + BAR_OFF + 8 * B_EMPTY;
            asm volatile("mapa.shared::cluster.u32 %0, %1, %2;" : "=r"(c.rel) : "r"(la), "r"(lane & 1));
            if (lane >= 2) c.rel = 0;
            asm volatile("" : "+r"(c.rel));
        }
        asm volatile("barrier.cluster.wait.acquire.aligned;" ::: "memory");
        const uint32_t tag = get_epoch(sbase) & 0xffffu;
        if (blockIdx.x < 128) {
            ln_x_row(xv, reinterpret_cast<uint4*>(g_xn + (size_t)r0 * D_) + (lane & 15), (lane & 15) ? nullptr : g_stat + r0, tag);
            fence_proxy_async_all();
        }
        asm volatile("bar.arrive 5, 288;" ::: "memory");
        if (c.wg == 1) asm volatile("bar.arrive 1, 256;" ::: "memory");
        asm volatile("st.volatile.shared.u32 [%0], 0;" :: "r"(sbase + BAR_OFF + 8 * (B_FLAG + c.wg)) : "memory");

        {
            const uint32_t row = c.wg * 64 + c.warp * 16 + (lane >> 1);
            const unsigned long long* sp = g_stat + (it_p(prm.sched[pair][0]) * 2 + rank) * 128 + row;
            unsigned long long sv;
            const uint32_t t0 = (uint32_t)clock();
            do {
                asm volatile("ld.relaxed.gpu.global.b64 %0, [%1];" : "=l"(sv) : "l"(sp) : "memory");
                if ((uint32_t)clock() - t0 > 2000000000u) die();
            } while (!__all_sync(0xffffffffu, ((uint32_t)(sv >> 32) & 0xffffu) == tag));
            const float r = __uint_as_float((uint32_t)sv);
            const uint32_t m2 = (uint32_t)(sv >> 48) * 0x10001u;
#pragma unroll
            for (uint32_t g = 0; g < NRAW; g++) {
                mbar_wait(sbase + BAR_OFF + 8 * (B_FULL + g), 0);
                uint32_t w[16];
#pragma unroll
                for (int i = 0; i < 4; i++)
                    asm volatile("ld.shared.v4.b32 {%0,%1,%2,%3}, [%4];" : "=r"(w[4 * i]), "=r"(w[4 * i + 1]), "=r"(w[4 * i + 2]), "=r"(w[4 * i + 3])
                                 : "r"(sbase + g * (3 * SLOT) + row * 128 + (lane & 1) * 64 + ((i + (lane >> 1)) & 3) * 16) : "memory");
#pragma unroll
                for (int i = 0; i < 4; i++)
                    asm volatile("st.shared.v4.b32 [%0], {%1,%2,%3,%4};"
                                 :: "r"(sbase + g * (3 * SLOT) + row * 128 + (lane & 1) * 64 + ((i + (lane >> 1)) & 3) * 16),
                                    "r"(ln_x_apply(w[4 * i], m2, r)), "r"(ln_x_apply(w[4 * i + 1], m2, r)),
                                    "r"(ln_x_apply(w[4 * i + 2], m2, r)), "r"(ln_x_apply(w[4 * i + 3], m2, r)) : "memory");
            }
            fence_proxy_async_smem();
            asm volatile("bar.sync %0, 128;" :: "r"(3 + c.wg) : "memory");
        }
        const uint32_t stash = sbase + STG_OFF + c.wg * SLOT + c.warp * 2048 + lane * 16;
        uint32_t pk[32];
#pragma unroll
        for (int i = 0; i < 32; i++) pk[i] = 0;
        uint32_t job = JOB_NONE;
        int ii = 0;
#pragma unroll 1
        for (; ii < MAX_ITEMS; ii++) {
            const uint32_t it = prm.sched[pair][ii];
            const uint32_t ty = it_type(it);
            if (ty == T_END) break;
            const uint32_t rb = it_p(it) * 2 + rank, j = it_j(it);
            const bool own = c.wg == (ty == T_FY);
            const uint32_t ncom = ty == T_FX ? 64 - it_k1(it) : it_k0(it) - it_kh(it);
            const uint32_t nkf = ncom + (own ? it_k1(it) - it_k0(it) : 0);
            uint32_t nk = ty == T_FX ? 28 : ty == T_FY ? nkf : ty == T_FH ? it_kh(it) : 16;
            uint32_t solo = ty == T_FY ? ncom : 999u;
            uint32_t bsp0 = 0, bsp1 = 0;
#pragma unroll 1
            for (int seg = 0; seg < 2; seg++) {
                float acc[128];
                gemm_main(c, acc, nk, job, pk, stash, ty == T_ATT, solo);
                job = JOB_NONE;
                if (ty == T_FY || (ty == T_FX && seg == 1)) {
                    if (own) {
                        const uint32_t base = stage_base(c);
                        __syncwarp();
                        if (ty == T_FY) {
                            mbar_wait<3>(sbase + BAR_OFF + 8 * B_GATE, 0);
#pragma unroll
                            for (int kk = 0; kk < 8; kk++) stage_get(base - SLOT, kk, pk[4 * kk], pk[4 * kk + 1], pk[4 * kk + 2], pk[4 * kk + 3]);
                        }
                        f_finish(c, base, pk, acc, it_kh(it) != 0, &prm.maps[M_OUT], rb * 128 + c.wg * 64, 4 * j);
                    } else {
                        uint4* dst = reinterpret_cast<uint4*>(g_part + (size_t)((rb * 4 + j) * 2 + c.wg) * 8192) + c.warp * 32 + lane_id();
#pragma unroll
                        for (int i = 0; i < 16; i++)
                            __stcg(dst + i * 128,
                                   make_uint4(pack_bf16(acc[8 * i], acc[8 * i + 1]), pack_bf16(acc[8 * i + 2], acc[8 * i + 3]),
                                              pack_bf16(acc[8 * i + 4], acc[8 * i + 5]), pack_bf16(acc[8 * i + 6], acc[8 * i + 7])));
                        fence_proxy_async_all();
                        __syncwarp();
                        if (lane_id() == 0) red_release(&g_cnt[C_PART + ((rb * 4 + j) * 2 + c.wg) * CS]);
                    }
                    break;
                }
                if (seg == 1) {
                    const uint32_t base = stage_base(c);
                    __syncwarp();
                    const uint32_t b0 = bsp0 * 0x10001u, b1 = bsp1 * 0x10001u;
                    uint32_t zl[32];
#pragma unroll
                    for (int kk = 0; kk < 8; kk++) stage_get(base, kk, zl[4 * kk], zl[4 * kk + 1], zl[4 * kk + 2], zl[4 * kk + 3]);
                    __syncwarp();
                    sp_half<0>(zl, acc, b0, b1);
#pragma unroll
                    for (int kk = 0; kk < 8; kk++) stage_put(base, kk, zl[4 * kk], zl[4 * kk + 1], zl[4 * kk + 2], zl[4 * kk + 3]);
                    sp_half<1>(pk, acc, b0, b1);
                    pin(pk);
                    stage_end(c);
                    job = JOB_PUB;
                    break;
                }
                if (ty == T_ATT) {
                    attention2(c, acc, stash);
#pragma unroll
                    for (int i = 0; i < 32; i++) pk[i] = 0;
                    break;
                }
                {
                    const uint32_t base = stage_begin(c);
#pragma unroll
                    for (int kk = 0; kk < 8; kk++)
                        stage_put(base, kk, pack_bf16(acc[64 + 8 * kk], acc[64 + 8 * kk + 1]), pack_bf16(acc[64 + 8 * kk + 2], acc[64 + 8 * kk + 3]),
                                  pack_bf16(acc[64 + 8 * kk + 4], acc[64 + 8 * kk + 5]), pack_bf16(acc[64 + 8 * kk + 6], acc[64 + 8 * kk + 7]));
#pragma unroll
                    for (int i = 0; i < 32; i++) pk[i] = pack_bf16(acc[2 * i], acc[2 * i + 1]);
                    __syncwarp();
                }
                if (ty == T_Z2) { job = JOB_GELU | JOB_PUB; break; }
                if (ty == T_FH) { stage_end(c); job = JOB_PUB; break; }
                if (ty == T_SP) {
                    const uint32_t r = rb * 128 + c.wg * 64 + c.warp * 16 + (lane_id() >> 2);
                    const unsigned short* bp = reinterpret_cast<const unsigned short*>(prm.b_sp);
                    bsp0 = __ldg(bp + r); bsp1 = __ldg(bp + r + 8);
                    job = JOB_GELU; nk = 32;
                } else {
                    job = own ? JOB_SILU : JOB_SILU | JOB_PUB; nk = nkf; solo = ncom;
                }
            }
        }
        if (job) stage_out(c, pk);
    }
    __syncwarp();
    asm volatile("barrier.cluster.arrive.relaxed.aligned;" ::: "memory");
    asm volatile("barrier.cluster.wait.aligned;" ::: "memory");
    if (threadIdx.x == 0) atomicAdd(&g_cnt[C_EXIT], 1u);
}

typedef CUresult (*EncodeFn)(CUtensorMap*, CUtensorMapDataType, cuuint32_t, void*, const cuuint64_t*, const cuuint64_t*,
                             const cuuint32_t*, const cuuint32_t*, CUtensorMapInterleave, CUtensorMapSwizzle,
                             CUtensorMapL2promotion, CUtensorMapFloatOOBfill);

static void make_2d(EncodeFn f, CUtensorMap* m, const void* p, uint64_t rows, uint64_t cols, uint32_t box_rows = 128) {
    cuuint64_t dims[2] = {cols, rows};
    cuuint64_t strides[1] = {cols * 2};
    cuuint32_t box[2] = {64, box_rows}, es[2] = {1, 1};
    f(m, CU_TENSOR_MAP_DATA_TYPE_BFLOAT16, 2, const_cast<void*>(p), dims, strides, box, es, CU_TENSOR_MAP_INTERLEAVE_NONE,
      CU_TENSOR_MAP_SWIZZLE_128B, CU_TENSOR_MAP_L2_PROMOTION_NONE, CU_TENSOR_MAP_FLOAT_OOB_FILL_NONE);
}
static void make_3d(EncodeFn f, CUtensorMap* m, const void* p, uint64_t rows, uint64_t cols) {
    cuuint64_t dims[3] = {64, rows, cols / 64};
    cuuint64_t strides[2] = {cols * 2, 128};
    cuuint32_t box[3] = {64, 64, 2}, es[3] = {1, 1, 1};
    f(m, CU_TENSOR_MAP_DATA_TYPE_BFLOAT16, 3, const_cast<void*>(p), dims, strides, box, es, CU_TENSOR_MAP_INTERLEAVE_NONE,
      CU_TENSOR_MAP_SWIZZLE_128B, CU_TENSOR_MAP_L2_PROMOTION_NONE, CU_TENSOR_MAP_FLOAT_OOB_FILL_NONE);
}

constexpr int KS_LATE = 43, KS_NORM = 45, KS_Z = 44, KS_HELP = 14, KS_SOLO = 4;
static void build_schedule(uint32_t (*sched)[MAX_ITEMS]) {
    int n[NPAIR];
    for (int i = 0; i < NPAIR; i++) { n[i] = 0; for (int k = 0; k < MAX_ITEMS; k++) sched[i][k] = T_END; }
    auto push = [&](int pr, uint32_t it) { sched[pr][n[pr]++] = it; };
    int z = 0;
    for (int pr = 0; pr < 8; pr++) { push(pr, mk_item(T_Z2, z / 7, z % 7)); z++; }
    for (int r = 0; r < 3; r++)
        for (int pr = 50; pr < 66; pr++) { push(pr, mk_item(T_Z2, z / 7, z % 7)); z++; }
    for (int pr = 0; pr < 64; pr++) push(pr, mk_item(T_ATT, pr % 8, pr / 8));
    for (int r = 0; r < 3; r++)
        for (int pr = 64; pr < 66; pr++) push(pr, mk_item(T_SP, 6 + (pr - 64), r));
    int pr_sp = 0;
    for (int j = 0; j < 7; j++)
        for (int p = 0; p < 8; p++)
            if (!(p >= 6 && j < 3)) push(pr_sp++, mk_item(T_SP, p, j));
    for (int pr = 0; pr < 64; pr++) push(pr, mk_item(T_ATT, pr % 8, 15 - pr / 8));
    for (int t = 0; t < 32; t++) {
        const int p = t % 8, nn = t / 8;
        const int y = t < 8 ? t : t + 32;
        const int ks = t < 8 ? KS_LATE : y < 50 ? KS_NORM : KS_Z;
        const int kh = t < 8 ? KS_HELP : 0;
        push(t + 8, mk_item(T_FX, p, nn, ks, ks + KS_SOLO, kh));
        push(y, mk_item(T_FY, p, nn, ks, ks + KS_SOLO, kh));
        if (kh) push(64 + (t & 1), mk_item(T_FH, p, 0, 0, 0, kh));
    }
}

extern "C" void kernel_launch(void* const* d_in, const int* in_sizes, int n_in, void* d_out, int out_size) {
    (void)in_sizes; (void)n_in; (void)out_size;
    static EncodeFn enc = nullptr;
    static void *p_xn, *p_z2, *p_o, *p_h, *p_help, *p_gate;
    if (!enc) {
        void* fn = nullptr;
        cudaDriverEntryPointQueryResult qr;
        cudaGetDriverEntryPoint("cuTensorMapEncodeTiled", &fn, cudaEnableDefault, &qr);
        enc = (EncodeFn)fn;
        cudaFuncSetAttribute(fused_kernel, cudaFuncAttributeMaxDynamicSharedMemorySize, SMEM_BYTES);
        cudaGetSymbolAddress(&p_xn, g_xn);
        cudaGetSymbolAddress(&p_z2, g_z2);
        cudaGetSymbolAddress(&p_o, g_o);
        cudaGetSymbolAddress(&p_h, g_h);
        cudaGetSymbolAddress(&p_help, g_help);
        cudaGetSymbolAddress(&p_gate, g_gate);
    }
    Params prm;
    make_2d(enc, &prm.maps[M_XN], p_xn, S_, D_);
    make_2d(enc, &prm.maps[M_XRAW], d_in[0], S_, D_);
    make_2d(enc, &prm.maps[M_WSP], d_in[7], S_, S_);
    make_2d(enc, &prm.maps[M_O_LD], p_o, S_, H_ * DH_);
    make_2d(enc, &prm.maps[M_O_LD64], p_o, S_, H_ * DH_, 64);
    make_2d(enc, &prm.maps[M_H_LD], p_h, S_, FH_);
    make_3d(enc, &prm.maps[M_X], d_in[0], S_, D_);
    make_2d(enc, &prm.maps[M_K], d_in[1], (uint64_t)H_ * S_, DH_);
    make_3d(enc, &prm.maps[M_WQ], d_in[3], D_, H_ * DH_);
    make_3d(enc, &prm.maps[M_WIN], d_in[6], D_, F_);
    make_3d(enc, &prm.maps[M_WO], d_in[4], H_ * DH_, D_);
    make_3d(enc, &prm.maps[M_WOUT], d_in[9], FH_, D_);
    make_3d(enc, &prm.maps[M_Z2], p_z2, S_, FH_);
    make_3d(enc, &prm.maps[M_V], d_in[2], (uint64_t)H_ * S_, DH_);
    make_3d(enc, &prm.maps[M_O_ST], p_o, S_, H_ * DH_);
    make_3d(enc, &prm.maps[M_H_ST], p_h, S_, FH_);
    make_3d(enc, &prm.maps[M_HELP], p_help, S_, 256);
    make_3d(enc, &prm.maps[M_GATE], p_gate, S_, D_);
    make_3d(enc, &prm.maps[M_OUT], d_out, S_, D_);
    prm.x = (const __nv_bfloat16*)d_in[0];
    prm.b_sp = (const __nv_bfloat16*)d_in[8];
    prm.zero = 0;
    build_schedule(prm.sched);
    fused_kernel<<<2 * NPAIR, 384, SMEM_BYTES>>>(prm);
}
```
